```python
import torch

def _softmax(x, axis=-1):
    return torch.softmax(x, dim=axis)
def _gelu(x):
    return torch.nn.functional.gelu(x, approximate="tanh")
def _silu(x):
    return torch.nn.functional.silu(x)
def _sigmoid(x):
    return torch.sigmoid(x)
def _layernorm(x, axis=-1, eps=1e-5):
    m = x.mean(dim=axis, keepdim=True)
    v = x.var(dim=axis, keepdim=True, unbiased=False)
    return (x - m) / torch.sqrt(v + eps)
def _scatter_add(tgt, idx, src, axis=0):
    return tgt.clone().index_add_(axis, idx, src)
def _segment_sum(src, seg, n):
    out = torch.zeros((n,) + src.shape[1:], dtype=src.dtype)
    return out.index_add_(0, seg, src)
def _pad(x, pw):
    flat = tuple(v for pair in reversed(pw) for v in pair)
    return torch.nn.functional.pad(x, flat)

kernel_name = 'interleave_layers__spectral_fnet__dense_activation_relu__prompt'

def setup_inputs():

    _w = (lambda a: (lambda t: t.to(torch.bfloat16) if t.is_floating_point() else t)(torch.as_tensor(a)))
    def _A_setup():
        B, S, D = 1, 2048, 576
        ns = torch.arange(S)[:, None] * torch.arange(S)[None, :]
        nd = torch.arange(D)[:, None] * torch.arange(D)[None, :]
        Ws_re = torch.cos(-2.0 * torch.pi * ns / S).to(float)
        Ws_im = torch.sin(-2.0 * torch.pi * ns / S).to(float)
        Wd_re = torch.cos(-2.0 * torch.pi * nd / D).to(float)
        Wd_im = torch.sin(-2.0 * torch.pi * nd / D).to(float)
        return {
            "x": _w((lambda *s: torch.randn(*s, dtype=torch.bfloat16) * 0.05)(B, S, D)),
            "dft_seq_re": _w(Ws_re),
            "dft_seq_im": _w(Ws_im),
            "dft_hid_re": _w(Wd_re),
            "dft_hid_im": _w(Wd_im),
        }
    _A_in = _A_setup()

    def _B_setup():
        B, S, D, Dff = 1, 2048, 576, 4608
        return {
            "x": _w((lambda *s: torch.randn(*s, dtype=torch.bfloat16) * 0.05)(B, S, D)),
            "w1": _w((lambda *s: torch.randn(*s, dtype=torch.bfloat16) * 1.6)(D, Dff)),
            "w2": _w((lambda *s: torch.randn(*s, dtype=torch.bfloat16) * 1.6)(Dff, D)),
        }
    _B_in = _B_setup()

    return {
        "A_x": _A_in["x"],
        "A_dft_seq_re": _A_in["dft_seq_re"],
        "A_dft_seq_im": _A_in["dft_seq_im"],
        "A_dft_hid_re": _A_in["dft_hid_re"],
        "A_dft_hid_im": _A_in["dft_hid_im"],
        "B_x": _B_in["x"],
        "B_w1": _B_in["w1"],
        "B_w2": _B_in["w2"],
    }

def reference(A_x, A_dft_seq_re, A_dft_seq_im, A_dft_hid_re, A_dft_hid_im, B_x, B_w1, B_w2):
    def _A_ref(x, dft_seq_re, dft_seq_im, dft_hid_re, dft_hid_im):
        a = torch.einsum("bsd,ed->bse", x, dft_hid_re)
        b = torch.einsum("bsd,ed->bse", x, dft_hid_im)
        y = torch.einsum("ts,bse->bte", dft_seq_re, a) - torch.einsum("ts,bse->bte", dft_seq_im, b)
        return y

    def _B_ref(x, w1, w2):
        h = torch.einsum("bsd,df->bsf", x, w1)
        zero = torch.zeros_like(h)
        h = torch.maximum(h, zero)
        return torch.einsum("bsf,fd->bsd", h, w2)

    x = A_x
    x = x + _A_ref(_layernorm(x, axis=-1), A_dft_seq_re, A_dft_seq_im, A_dft_hid_re, A_dft_hid_im)
    x = x + _B_ref(_layernorm(x, axis=-1), B_w1, B_w2)
    x = x + _A_ref(_layernorm(x, axis=-1), A_dft_seq_re, A_dft_seq_im, A_dft_hid_re, A_dft_hid_im)
    x = x + _B_ref(_layernorm(x, axis=-1), B_w1, B_w2)
    return x
```

```cpp
#include <cuda_runtime.h>
#include <cuda_bf16.h>
#include <cuda.h>
#include <stdint.h>

namespace {

constexpr int SEQ = 2048, DM = 576, DFF = 4608;
constexpr int NHELP = 4, NWORK = 128, NGRID = NHELP + NWORK;

constexpr int A_SLOT = 16384, B_SLOT = 12288, NB = 5, LSTEPS = 174;
constexpr int OFF_A = 0;
constexpr int OFF_B = 9 * A_SLOT;
constexpr int OFF_STG = OFF_B + NB * B_SLOT;
constexpr int OFF_STAT = OFF_STG;
constexpr int OFF_CS1 = OFF_STG + 1024;
constexpr int OFF_CSD = OFF_STG + 16384;
constexpr int OFF_EPOCH = OFF_CSD + 576;
constexpr int OFF_RS = OFF_CSD + 640;
constexpr int OFF_BAR = OFF_RS + 512;
constexpr int SMEM_BYTES = 232448;

constexpr int BAR_BFULL = 0  , BAR_BEMPTY = 12, BAR_XF = 18, BAR_CF = 27, BAR_X1F = 36  , BAR_HF = 51,
              BAR_RG1 = 60, BAR_RG2 = 69, BAR_RG3B = 78, BAR_RG3C = 87, BAR_RG4 = 96, BAR_RNONE = 105  ,
              BAR_STAT = 114  , BAR_ABSTG = 116  , BAR_FOK = 118  , BAR_EPOCH = 120, BAR_CSD = 121,
              BAR_ABOK = 122  , BAR_FDONE = 126  , BAR_GO = 144  , BAR_XOK = 162  , NBAR = 180;
static_assert(OFF_BAR + NBAR * 8 <= SMEM_BYTES, "smem");

constexpr int CNT_STRIDE = 32;
constexpr int CNT_AB = 0;
constexpr int CNT_X = 128;
constexpr int CNT_XINIT = CNT_X + 432;
constexpr int CNT_G3 = CNT_XINIT + 16;
constexpr int CNT_CS = CNT_G3 + 32;
constexpr int CNT_TICKET = CNT_CS + 1;
constexpr int NCNT = CNT_TICKET + 1;

__device__ uint32_t g_cnt[NCNT * CNT_STRIDE];
__device__ __nv_bfloat16 g_ab[2 * 2 * SEQ * DM];
__device__ float g_cs1[DFF];
__device__ __align__(16) unsigned long long g_csd[8 * 144];
__device__ ulonglong2 g_stat[4 * SEQ];
#define TL(i)
#define EV(i)
#define EVE(i)

template <int V> struct IntT { static constexpr int value = V; };
struct TrueT { static constexpr bool value = true; };
struct FalseT { static constexpr bool value = false; };

struct Maps {
  CUtensorMap xin, xld, xred, cr, ci, dr, di, abld, abst, w1, w2, w2n;
};

template<int TB, bool FIRST, int TA = 0> __device__ __forceinline__ void wgmma_n128(float (&d)[64], uint64_t da, uint64_t db){
  if (FIRST) {
    asm volatile("wgmma.mma_async.sync.aligned.m64n128k16.f32.bf16.bf16 {%0, %1, %2, %3, %4, %5, %6, %7, %8, %9, %10, %11, %12, %13, %14, %15, %16, %17, %18, %19, %20, %21, %22, %23, %24, %25, %26, %27, %28, %29, %30, %31, %32, %33, %34, %35, %36, %37, %38, %39, %40, %41, %42, %43, %44, %45, %46, %47, %48, %49, %50, %51, %52, %53, %54, %55, %56, %57, %58, %59, %60, %61, %62, %63}, %64, %65, 0, 1, 1, %67, %66;"
     : "=f"(d[0]), "=f"(d[1]), "=f"(d[2]), "=f"(d[3]), "=f"(d[4]), "=f"(d[5]), "=f"(d[6]), "=f"(d[7]), "=f"(d[8]), "=f"(d[9]), "=f"(d[10]), "=f"(d[11]), "=f"(d[12]), "=f"(d[13]), "=f"(d[14]), "=f"(d[15]), "=f"(d[16]), "=f"(d[17]), "=f"(d[18]), "=f"(d[19]), "=f"(d[20]), "=f"(d[21]), "=f"(d[22]), "=f"(d[23]), "=f"(d[24]), "=f"(d[25]), "=f"(d[26]), "=f"(d[27]), "=f"(d[28]), "=f"(d[29]), "=f"(d[30]), "=f"(d[31]), "=f"(d[32]), "=f"(d[33]), "=f"(d[34]), "=f"(d[35]), "=f"(d[36]), "=f"(d[37]), "=f"(d[38]), "=f"(d[39]), "=f"(d[40]), "=f"(d[41]), "=f"(d[42]), "=f"(d[43]), "=f"(d[44]), "=f"(d[45]), "=f"(d[46]), "=f"(d[47]), "=f"(d[48]), "=f"(d[49]), "=f"(d[50]), "=f"(d[51]), "=f"(d[52]), "=f"(d[53]), "=f"(d[54]), "=f"(d[55]), "=f"(d[56]), "=f"(d[57]), "=f"(d[58]), "=f"(d[59]), "=f"(d[60]), "=f"(d[61]), "=f"(d[62]), "=f"(d[63])
     : "l"(da), "l"(db), "n"(TB), "n"(TA));
  } else {
    asm volatile("wgmma.mma_async.sync.aligned.m64n128k16.f32.bf16.bf16 {%0, %1, %2, %3, %4, %5, %6, %7, %8, %9, %10, %11, %12, %13, %14, %15, %16, %17, %18, %19, %20, %21, %22, %23, %24, %25, %26, %27, %28, %29, %30, %31, %32, %33, %34, %35, %36, %37, %38, %39, %40, %41, %42, %43, %44, %45, %46, %47, %48, %49, %50, %51, %52, %53, %54, %55, %56, %57, %58, %59, %60, %61, %62, %63}, %64, %65, 1, 1, 1, %67, %66;"
     : "+f"(d[0]), "+f"(d[1]), "+f"(d[2]), "+f"(d[3]), "+f"(d[4]), "+f"(d[5]), "+f"(d[6]), "+f"(d[7]), "+f"(d[8]), "+f"(d[9]), "+f"(d[10]), "+f"(d[11]), "+f"(d[12]), "+f"(d[13]), "+f"(d[14]), "+f"(d[15]), "+f"(d[16]), "+f"(d[17]), "+f"(d[18]), "+f"(d[19]), "+f"(d[20]), "+f"(d[21]), "+f"(d[22]), "+f"(d[23]), "+f"(d[24]), "+f"(d[25]), "+f"(d[26]), "+f"(d[27]), "+f"(d[28]), "+f"(d[29]), "+f"(d[30]), "+f"(d[31]), "+f"(d[32]), "+f"(d[33]), "+f"(d[34]), "+f"(d[35]), "+f"(d[36]), "+f"(d[37]), "+f"(d[38]), "+f"(d[39]), "+f"(d[40]), "+f"(d[41]), "+f"(d[42]), "+f"(d[43]), "+f"(d[44]), "+f"(d[45]), "+f"(d[46]), "+f"(d[47]), "+f"(d[48]), "+f"(d[49]), "+f"(d[50]), "+f"(d[51]), "+f"(d[52]), "+f"(d[53]), "+f"(d[54]), "+f"(d[55]), "+f"(d[56]), "+f"(d[57]), "+f"(d[58]), "+f"(d[59]), "+f"(d[60]), "+f"(d[61]), "+f"(d[62]), "+f"(d[63])
     : "l"(da), "l"(db), "n"(TB), "n"(TA));
  }
}
template<int TB, bool FIRST, int TA = 0> __device__ __forceinline__ void wgmma_n144(float (&d)[72], uint64_t da, uint64_t db){
  if (FIRST) {
    asm volatile("wgmma.mma_async.sync.aligned.m64n144k16.f32.bf16.bf16 {%0, %1, %2, %3, %4, %5, %6, %7, %8, %9, %10, %11, %12, %13, %14, %15, %16, %17, %18, %19, %20, %21, %22, %23, %24, %25, %26, %27, %28, %29, %30, %31, %32, %33, %34, %35, %36, %37, %38, %39, %40, %41, %42, %43, %44, %45, %46, %47, %48, %49, %50, %51, %52, %53, %54, %55, %56, %57, %58, %59, %60, %61, %62, %63, %64, %65, %66, %67, %68, %69, %70, %71}, %72, %73, 0, 1, 1, %75, %74;"
     : "=f"(d[0]), "=f"(d[1]), "=f"(d[2]), "=f"(d[3]), "=f"(d[4]), "=f"(d[5]), "=f"(d[6]), "=f"(d[7]), "=f"(d[8]), "=f"(d[9]), "=f"(d[10]), "=f"(d[11]), "=f"(d[12]), "=f"(d[13]), "=f"(d[14]), "=f"(d[15]), "=f"(d[16]), "=f"(d[17]), "=f"(d[18]), "=f"(d[19]), "=f"(d[20]), "=f"(d[21]), "=f"(d[22]), "=f"(d[23]), "=f"(d[24]), "=f"(d[25]), "=f"(d[26]), "=f"(d[27]), "=f"(d[28]), "=f"(d[29]), "=f"(d[30]), "=f"(d[31]), "=f"(d[32]), "=f"(d[33]), "=f"(d[34]), "=f"(d[35]), "=f"(d[36]), "=f"(d[37]), "=f"(d[38]), "=f"(d[39]), "=f"(d[40]), "=f"(d[41]), "=f"(d[42]), "=f"(d[43]), "=f"(d[44]), "=f"(d[45]), "=f"(d[46]), "=f"(d[47]), "=f"(d[48]), "=f"(d[49]), "=f"(d[50]), "=f"(d[51]), "=f"(d[52]), "=f"(d[53]), "=f"(d[54]), "=f"(d[55]), "=f"(d[56]), "=f"(d[57]), "=f"(d[58]), "=f"(d[59]), "=f"(d[60]), "=f"(d[61]), "=f"(d[62]), "=f"(d[63]), "=f"(d[64]), "=f"(d[65]), "=f"(d[66]), "=f"(d[67]), "=f"(d[68]), "=f"(d[69]), "=f"(d[70]), "=f"(d[71])
     : "l"(da), "l"(db), "n"(TB), "n"(TA));
  } else {
    asm volatile("wgmma.mma_async.sync.aligned.m64n144k16.f32.bf16.bf16 {%0, %1, %2, %3, %4, %5, %6, %7, %8, %9, %10, %11, %12, %13, %14, %15, %16, %17, %18, %19, %20, %21, %22, %23, %24, %25, %26, %27, %28, %29, %30, %31, %32, %33, %34, %35, %36, %37, %38, %39, %40, %41, %42, %43, %44, %45, %46, %47, %48, %49, %50, %51, %52, %53, %54, %55, %56, %57, %58, %59, %60, %61, %62, %63, %64, %65, %66, %67, %68, %69, %70, %71}, %72, %73, 1, 1, 1, %75, %74;"
     : "+f"(d[0]), "+f"(d[1]), "+f"(d[2]), "+f"(d[3]), "+f"(d[4]), "+f"(d[5]), "+f"(d[6]), "+f"(d[7]), "+f"(d[8]), "+f"(d[9]), "+f"(d[10]), "+f"(d[11]), "+f"(d[12]), "+f"(d[13]), "+f"(d[14]), "+f"(d[15]), "+f"(d[16]), "+f"(d[17]), "+f"(d[18]), "+f"(d[19]), "+f"(d[20]), "+f"(d[21]), "+f"(d[22]), "+f"(d[23]), "+f"(d[24]), "+f"(d[25]), "+f"(d[26]), "+f"(d[27]), "+f"(d[28]), "+f"(d[29]), "+f"(d[30]), "+f"(d[31]), "+f"(d[32]), "+f"(d[33]), "+f"(d[34]), "+f"(d[35]), "+f"(d[36]), "+f"(d[37]), "+f"(d[38]), "+f"(d[39]), "+f"(d[40]), "+f"(d[41]), "+f"(d[42]), "+f"(d[43]), "+f"(d[44]), "+f"(d[45]), "+f"(d[46]), "+f"(d[47]), "+f"(d[48]), "+f"(d[49]), "+f"(d[50]), "+f"(d[51]), "+f"(d[52]), "+f"(d[53]), "+f"(d[54]), "+f"(d[55]), "+f"(d[56]), "+f"(d[57]), "+f"(d[58]), "+f"(d[59]), "+f"(d[60]), "+f"(d[61]), "+f"(d[62]), "+f"(d[63]), "+f"(d[64]), "+f"(d[65]), "+f"(d[66]), "+f"(d[67]), "+f"(d[68]), "+f"(d[69]), "+f"(d[70]), "+f"(d[71])
     : "l"(da), "l"(db), "n"(TB), "n"(TA));
  }
}
template<int TB, bool FIRST, int TA = 0> __device__ __forceinline__ void wgmma_n192(float (&d)[96], uint64_t da, uint64_t db){
  if (FIRST) {
    asm volatile("wgmma.mma_async.sync.aligned.m64n192k16.f32.bf16.bf16 {%0, %1, %2, %3, %4, %5, %6, %7, %8, %9, %10, %11, %12, %13, %14, %15, %16, %17, %18, %19, %20, %21, %22, %23, %24, %25, %26, %27, %28, %29, %30, %31, %32, %33, %34, %35, %36, %37, %38, %39, %40, %41, %42, %43, %44, %45, %46, %47, %48, %49, %50, %51, %52, %53, %54, %55, %56, %57, %58, %59, %60, %61, %62, %63, %64, %65, %66, %67, %68, %69, %70, %71, %72, %73, %74, %75, %76, %77, %78, %79, %80, %81, %82, %83, %84, %85, %86, %87, %88, %89, %90, %91, %92, %93, %94, %95}, %96, %97, 0, 1, 1, %99, %98;"
     : "=f"(d[0]), "=f"(d[1]), "=f"(d[2]), "=f"(d[3]), "=f"(d[4]), "=f"(d[5]), "=f"(d[6]), "=f"(d[7]), "=f"(d[8]), "=f"(d[9]), "=f"(d[10]), "=f"(d[11]), "=f"(d[12]), "=f"(d[13]), "=f"(d[14]), "=f"(d[15]), "=f"(d[16]), "=f"(d[17]), "=f"(d[18]), "=f"(d[19]), "=f"(d[20]), "=f"(d[21]), "=f"(d[22]), "=f"(d[23]), "=f"(d[24]), "=f"(d[25]), "=f"(d[26]), "=f"(d[27]), "=f"(d[28]), "=f"(d[29]), "=f"(d[30]), "=f"(d[31]), "=f"(d[32]), "=f"(d[33]), "=f"(d[34]), "=f"(d[35]), "=f"(d[36]), "=f"(d[37]), "=f"(d[38]), "=f"(d[39]), "=f"(d[40]), "=f"(d[41]), "=f"(d[42]), "=f"(d[43]), "=f"(d[44]), "=f"(d[45]), "=f"(d[46]), "=f"(d[47]), "=f"(d[48]), "=f"(d[49]), "=f"(d[50]), "=f"(d[51]), "=f"(d[52]), "=f"(d[53]), "=f"(d[54]), "=f"(d[55]), "=f"(d[56]), "=f"(d[57]), "=f"(d[58]), "=f"(d[59]), "=f"(d[60]), "=f"(d[61]), "=f"(d[62]), "=f"(d[63]), "=f"(d[64]), "=f"(d[65]), "=f"(d[66]), "=f"(d[67]), "=f"(d[68]), "=f"(d[69]), "=f"(d[70]), "=f"(d[71]), "=f"(d[72]), "=f"(d[73]), "=f"(d[74]), "=f"(d[75]), "=f"(d[76]), "=f"(d[77]), "=f"(d[78]), "=f"(d[79]), "=f"(d[80]), "=f"(d[81]), "=f"(d[82]), "=f"(d[83]), "=f"(d[84]), "=f"(d[85]), "=f"(d[86]), "=f"(d[87]), "=f"(d[88]), "=f"(d[89]), "=f"(d[90]), "=f"(d[91]), "=f"(d[92]), "=f"(d[93]), "=f"(d[94]), "=f"(d[95])
     : "l"(da), "l"(db), "n"(TB), "n"(TA));
  } else {
    asm volatile("wgmma.mma_async.sync.aligned.m64n192k16.f32.bf16.bf16 {%0, %1, %2, %3, %4, %5, %6, %7, %8, %9, %10, %11, %12, %13, %14, %15, %16, %17, %18, %19, %20, %21, %22, %23, %24, %25, %26, %27, %28, %29, %30, %31, %32, %33, %34, %35, %36, %37, %38, %39, %40, %41, %42, %43, %44, %45, %46, %47, %48, %49, %50, %51, %52, %53, %54, %55, %56, %57, %58, %59, %60, %61, %62, %63, %64, %65, %66, %67, %68, %69, %70, %71, %72, %73, %74, %75, %76, %77, %78, %79, %80, %81, %82, %83, %84, %85, %86, %87, %88, %89, %90, %91, %92, %93, %94, %95}, %96, %97, 1, 1, 1, %99, %98;"
     : "+f"(d[0]), "+f"(d[1]), "+f"(d[2]), "+f"(d[3]), "+f"(d[4]), "+f"(d[5]), "+f"(d[6]), "+f"(d[7]), "+f"(d[8]), "+f"(d[9]), "+f"(d[10]), "+f"(d[11]), "+f"(d[12]), "+f"(d[13]), "+f"(d[14]), "+f"(d[15]), "+f"(d[16]), "+f"(d[17]), "+f"(d[18]), "+f"(d[19]), "+f"(d[20]), "+f"(d[21]), "+f"(d[22]), "+f"(d[23]), "+f"(d[24]), "+f"(d[25]), "+f"(d[26]), "+f"(d[27]), "+f"(d[28]), "+f"(d[29]), "+f"(d[30]), "+f"(d[31]), "+f"(d[32]), "+f"(d[33]), "+f"(d[34]), "+f"(d[35]), "+f"(d[36]), "+f"(d[37]), "+f"(d[38]), "+f"(d[39]), "+f"(d[40]), "+f"(d[41]), "+f"(d[42]), "+f"(d[43]), "+f"(d[44]), "+f"(d[45]), "+f"(d[46]), "+f"(d[47]), "+f"(d[48]), "+f"(d[49]), "+f"(d[50]), "+f"(d[51]), "+f"(d[52]), "+f"(d[53]), "+f"(d[54]), "+f"(d[55]), "+f"(d[56]), "+f"(d[57]), "+f"(d[58]), "+f"(d[59]), "+f"(d[60]), "+f"(d[61]), "+f"(d[62]), "+f"(d[63]), "+f"(d[64]), "+f"(d[65]), "+f"(d[66]), "+f"(d[67]), "+f"(d[68]), "+f"(d[69]), "+f"(d[70]), "+f"(d[71]), "+f"(d[72]), "+f"(d[73]), "+f"(d[74]), "+f"(d[75]), "+f"(d[76]), "+f"(d[77]), "+f"(d[78]), "+f"(d[79]), "+f"(d[80]), "+f"(d[81]), "+f"(d[82]), "+f"(d[83]), "+f"(d[84]), "+f"(d[85]), "+f"(d[86]), "+f"(d[87]), "+f"(d[88]), "+f"(d[89]), "+f"(d[90]), "+f"(d[91]), "+f"(d[92]), "+f"(d[93]), "+f"(d[94]), "+f"(d[95])
     : "l"(da), "l"(db), "n"(TB), "n"(TA));
  }
}

__device__ __forceinline__ uint32_t clock32() { uint32_t t; asm volatile("mov.u32 %0, %%clock;" : "=r"(t)); return t; }
__device__ __forceinline__ bool elect_one() {
  uint32_t pred;
  asm volatile("{\n.reg .pred p;\nelect.sync _|p, 0xffffffff;\nselp.u32 %0, 1, 0, p;\n}" : "=r"(pred));
  return pred != 0;
}
__device__ __forceinline__ void mbar_init(uint32_t b, int c) { asm volatile("mbarrier.init.shared::cta.b64 [%0], %1;" ::"r"(b), "r"(c)); }
__device__ __forceinline__ void mbar_expect(uint32_t b, int bytes) { asm volatile("mbarrier.arrive.expect_tx.shared::cta.b64 _, [%0], %1;" ::"r"(b), "r"(bytes) : "memory"); }
__device__ __forceinline__ void mbar_arrive(uint32_t b) { asm volatile("mbarrier.arrive.shared::cta.b64 _, [%0];" ::"r"(b) : "memory"); }
__device__ __forceinline__ void mbar_arrive_if(uint32_t b, uint32_t pred) {
  asm volatile("{\n.reg .pred p;\nsetp.ne.u32 p, %1, 0;\n@p mbarrier.arrive.shared::cta.b64 _, [%0];\n}" ::"r"(b), "r"(pred) : "memory");
}
#define WAIT_LIMIT "2000000"
#define DIE_ADDR "l"(0ull)
#define DIE_ST "st.global.u32 [%2], %1;\n"
__device__ __forceinline__ void mbar_wait(uint32_t b, uint32_t ph) {
  asm volatile(
      "{\n.reg .pred p;\n.reg .u32 c;\nmov.u32 c, 0;\n"
      "W:\nmbarrier.try_wait.parity.shared::cta.b64 p, [%0], %1, 1000;\n@p bra D;\n"
      "add.u32 c, c, 1;\nsetp.lt.u32 p, c, " WAIT_LIMIT ";\n@p bra W;\n" DIE_ST
      "D:\n}" ::"r"(b), "r"(ph), DIE_ADDR : "memory");
}
__device__ __forceinline__ uint32_t mbar_test(uint32_t b, uint32_t ph) {
  uint32_t ok;
  asm volatile("{\n.reg .pred p;\nmbarrier.test_wait.parity.shared::cta.b64 p, [%1], %2;\nselp.u32 %0, 1, 0, p;\n}" : "=r"(ok) : "r"(b), "r"(ph) : "memory");
  return ok;
}
__device__ __forceinline__ void cnt_arrive(int idx) {
  asm volatile("red.release.gpu.global.add.u32 [%0], 1;" ::"l"(&g_cnt[idx * CNT_STRIDE]) : "memory");
}
__device__ __forceinline__ void cnt_wait(uint32_t idx, uint32_t target) {
  asm volatile(
      "{\n.reg .pred p;\n.reg .u32 c, v;\nmov.u32 c, 0;\n"
      "W:\nld.acquire.gpu.global.u32 v, [%3];\nsub.u32 v, v, %1;\nsetp.ge.s32 p, v, 0;\n@p bra D;\n"
      "add.u32 c, c, 1;\nsetp.lt.u32 p, c, " WAIT_LIMIT ";\n@p bra W;\n" DIE_ST
      "D:\n}" ::"r"(idx | 0x80000000u), "r"(target), DIE_ADDR, "l"(&g_cnt[idx * CNT_STRIDE]) : "memory");
}
__device__ __forceinline__ void release_x(uint32_t fdone, uint32_t ph, int cnt, int n, uint32_t mask, int ev) {
#pragma unroll 1
  for (int k = 0; k < n;) {
    int e = k + __ffs(mask >> k);
    mbar_wait(fdone + 8 * (e - 1), ph);
#pragma unroll 1
    while (e < n && mbar_test(fdone + 8 * e, ph)) e++;
    if (ev) for (int j = k; j < e; j++) EV(32 + j);
    asm volatile("fence.release.gpu;" ::: "memory");
#pragma unroll 1
    for (; k < e; k++) {
      asm volatile("red.relaxed.gpu.global.add.u32 [%0], 1;" ::"l"(&g_cnt[(cnt + k) * CNT_STRIDE]) : "memory");
      if (ev) EV(48 + k);
    }
  }
}
__device__ __forceinline__ uint4 lds128(uint32_t a) {
  uint4 v;
  asm volatile("ld.shared.v4.u32 {%0,%1,%2,%3}, [%4];" : "=r"(v.x), "=r"(v.y), "=r"(v.z), "=r"(v.w) : "r"(a) : "memory");
  return v;
}
__device__ __forceinline__ void stat_publish(ulonglong2* p, float s, float qq, uint32_t ep1) {
  const float mean = s * (1.0f / DM);
  const float rstd = rsqrtf(fmaxf(qq * (1.0f / DM) - mean * mean, 0.f) + 1e-5f);
  const unsigned long long tag = (unsigned long long)ep1 << 32;
  asm volatile("st.relaxed.gpu.global.v2.u64 [%0], {%1, %2};" ::"l"(p), "l"(tag | __float_as_uint(rstd)), "l"(tag | __float_as_uint(-mean)) : "memory");
}
__device__ __forceinline__ void stat_gather(const ulonglong2* p, uint32_t tag, float2* dst, float* rsd) {
  unsigned long long a[4], b[4];
#pragma unroll 1
  for (uint32_t it = 0;; it++) {
    bool ok = true;
#pragma unroll
    for (int i = 0; i < 4; i++) asm volatile("ld.relaxed.gpu.global.v2.u64 {%0, %1}, [%2];" : "=l"(a[i]), "=l"(b[i]) : "l"(p + i * 32) : "memory");
#pragma unroll
    for (int i = 0; i < 4; i++) ok = ok && (uint32_t)(a[i] >> 32) == tag && (uint32_t)(b[i] >> 32) == tag;
    if (ok) break;
    if (it > 2000000u) { asm volatile("st.global.u32 [%0], %1;" ::"l"(0ull), "r"(0) : "memory"); break; }
  }
#pragma unroll
  for (int i = 0; i < 4; i++) {
    dst[i * 32] = make_float2(__uint_as_float((uint32_t)a[i]), __uint_as_float((uint32_t)b[i]));
    rsd[i * 32] = __uint_as_float((uint32_t)a[i]);
  }
}
__device__ __forceinline__ void pace(uint32_t t0, uint32_t dt) { while (clock32() - t0 < dt) __nanosleep(20); }
__device__ __forceinline__ void spin_until(uint32_t t) {
  asm volatile("{\n.reg .pred p;\n.reg .u32 c;\nW:\nmov.u32 c, %%clock;\nsub.u32 c, c, %0;\nsetp.lt.s32 p, c, 0;\n@p nanosleep.u32 40;\n@p bra W;\n}" ::"r"(t) : "memory");
}
__device__ __forceinline__ void tma2d(uint32_t dst, const CUtensorMap* m, uint32_t bar, int c0, int c1) {
  asm volatile("cp.async.bulk.tensor.2d.shared::cluster.global.mbarrier::complete_tx::bytes [%0], [%1, {%3, %4}], [%2];" ::"r"(dst), "l"(m), "r"(bar), "r"(c0), "r"(c1) : "memory");
}
__device__ __forceinline__ void tma2d_ef(uint32_t dst, const CUtensorMap* m, uint32_t bar, int c0, int c1) {
  asm volatile("{\n.reg .b64 pol;\ncreatepolicy.fractional.L2::evict_first.b64 pol, 1.0;\n"
               "cp.async.bulk.tensor.2d.shared::cluster.global.mbarrier::complete_tx::bytes.L2::cache_hint [%0], [%1, {%3, %4}], [%2], pol;\n}"
               ::"r"(dst), "l"(m), "r"(bar), "r"(c0), "r"(c1) : "memory");
}
__device__ __forceinline__ void tma3d(uint32_t dst, const CUtensorMap* m, uint32_t bar, int c0, int c1, int c2) {
  asm volatile("cp.async.bulk.tensor.3d.shared::cluster.global.mbarrier::complete_tx::bytes [%0], [%1, {%3, %4, %5}], [%2];" ::"r"(dst), "l"(m), "r"(bar), "r"(c0), "r"(c1), "r"(c2) : "memory");
}
__device__ __forceinline__ void bulk_pf(const void* p, int bytes) {
  asm volatile("cp.async.bulk.prefetch.L2.global [%0], %1;" ::"l"(p), "r"(bytes) : "memory");
}
__device__ __forceinline__ void tma_st2d(const CUtensorMap* m, uint32_t src, int c0, int c1) {
  asm volatile("cp.async.bulk.tensor.2d.global.shared::cta.tile.bulk_group [%0, {%2, %3}], [%1];" ::"l"(m), "r"(src), "r"(c0), "r"(c1) : "memory");
}
__device__ __forceinline__ void tma_red2d(const CUtensorMap* m, uint32_t src, int c0, int c1) {
  asm volatile("cp.reduce.async.bulk.tensor.2d.global.shared::cta.add.tile.bulk_group [%0, {%2, %3}], [%1];" ::"l"(m), "r"(src), "r"(c0), "r"(c1) : "memory");
}
__device__ __forceinline__ void bulk_commit() { asm volatile("cp.async.bulk.commit_group;" ::: "memory"); }
__device__ __forceinline__ void bulk_wait0() { asm volatile("cp.async.bulk.wait_group 0;" ::: "memory"); }
__device__ __forceinline__ void fence_async_smem() { asm volatile("fence.proxy.async.shared::cta;" ::: "memory"); }
__device__ __forceinline__ void fence_async_all() { asm volatile("fence.proxy.async.global;" ::: "memory"); }
__device__ __forceinline__ void wg_fence() { asm volatile("wgmma.fence.sync.aligned;" ::: "memory"); }
__device__ __forceinline__ void wg_commit() { asm volatile("wgmma.commit_group.sync.aligned;" ::: "memory"); }
template <int N> __device__ __forceinline__ void wg_wait() { asm volatile("wgmma.wait_group.sync.aligned %0;" ::"n"(N) : "memory"); }
__device__ __forceinline__ uint32_t pk(float a, float b) {
  uint32_t r;
  asm("cvt.rn.bf16x2.f32 %0, %1, %2;" : "=r"(r) : "f"(b), "f"(a));
  return r;
}
__device__ __forceinline__ uint32_t pk_relu(float a, float b) {
  uint32_t r;
  asm("cvt.rn.relu.bf16x2.f32 %0, %1, %2;" : "=r"(r) : "f"(b), "f"(a));
  return r;
}
__device__ __forceinline__ float bf_lo(uint32_t v) { return __uint_as_float(v << 16); }
__device__ __forceinline__ float bf_hi(uint32_t v) { return __uint_as_float(v & 0xffff0000u); }
__device__ __forceinline__ void stsm4(uint32_t addr, uint32_t a0, uint32_t a1, uint32_t a2, uint32_t a3) {
  asm volatile("stmatrix.sync.aligned.m8n8.x4.shared.b16 [%0], {%1,%2,%3,%4};" ::"r"(addr), "r"(a0), "r"(a1), "r"(a2), "r"(a3));
}
__device__ __forceinline__ float2 lds64f(uint32_t a) {
  float2 v;
  asm volatile("ld.shared.v2.f32 {%0,%1}, [%2];" : "=f"(v.x), "=f"(v.y) : "r"(a) : "memory");
  return v;
}
template <int R> __device__ __forceinline__ void reg_fence(float (&d)[R]) {
#pragma unroll
  for (int i = 0; i < R; i++) asm volatile("" : "+f"(d[i])::"memory");
}
constexpr uint32_t DESC_HI_128 = (1024u >> 4) | (1u << 30);
constexpr uint32_t DESC_HI_64 = (512u >> 4) | (2u << 30);
__device__ __forceinline__ uint64_t desc(uint32_t lo, uint32_t hi) {
  uint64_t d;
  asm("mov.b64 %0, {%1, %2};" : "=l"(d) : "r"(lo), "r"(hi));
  return d;
}

__device__ __forceinline__ void sum8(uint4 v, float& s, float& q) {
  float a;
  a = bf_lo(v.x); s += a; q = fmaf(a, a, q);  a = bf_hi(v.x); s += a; q = fmaf(a, a, q);
  a = bf_lo(v.y); s += a; q = fmaf(a, a, q);  a = bf_hi(v.y); s += a; q = fmaf(a, a, q);
  a = bf_lo(v.z); s += a; q = fmaf(a, a, q);  a = bf_hi(v.z); s += a; q = fmaf(a, a, q);
  a = bf_lo(v.w); s += a; q = fmaf(a, a, q);  a = bf_hi(v.w); s += a; q = fmaf(a, a, q);
}

#define G3B_CUT_ 10
constexpr int G3A_CUT = 12, G3B_CUT = G3B_CUT_;
#define MAPMODE 0
#define CLUSTER 2
#define CPF_DT 450
#define CPF_LAG 3
#define CPF_START 0
#define CLD_DT 650
#define FLUSH_DT 750
#define FLUSH_DT_LAST 0
#define STAGGER 1
#define FRONT 0
#define EVPH 2
#define FLUSH_DT_D 300
#define HW1_START 14000
#define HPF_C_START 44000
#define XEARLY2 3
#define XEARLY4 4
#define FLUSH_DT4 200
#define RELMASK2 0x16C
#define RELMASK4 0xAA
#define FLUSH_DT_C 750
#define CEARLY 2
#define XLD_DT 500

__global__ void __launch_bounds__(384, 1)
fnet_ffn_kernel(const __grid_constant__ Maps maps, const __nv_bfloat16* __restrict__ xin, const __nv_bfloat16* __restrict__ cre,
                const __nv_bfloat16* __restrict__ cim, const __nv_bfloat16* __restrict__ dre,
                const __nv_bfloat16* __restrict__ dim, const __nv_bfloat16* __restrict__ w1, const __nv_bfloat16* __restrict__ w2,
                __nv_bfloat16* xout) {
  extern __shared__ __align__(1024) unsigned char smem[];
  const uint32_t sb = __shfl_sync(0xffffffffu, (uint32_t)__cvta_generic_to_shared(smem), 0);
  constexpr uint32_t sbd = 1024;
  const int tid = threadIdx.x;
  const int wg = __shfl_sync(0xffffffffu, tid >> 7, 0);
  const int warp = __shfl_sync(0xffffffffu, (tid >> 5) & 3, 0);
  const int lane = tid & 31;
  if (blockIdx.x < NHELP) {
    if (tid == 0) atomicAdd(&g_cnt[CNT_TICKET * CNT_STRIDE], 1u);
    const uint32_t th0 = clock32();
    constexpr int HS = 16, HG = DFF / 192 / NHELP;
    const uint32_t hb = sb + HS * B_SLOT + 8192;
    if (tid < 2 * HS) { mbar_init(hb + 8 * tid, 1); asm volatile("fence.mbarrier_init.release.cluster;" ::: "memory"); }
    for (int i = tid; i < 2048; i += 384) reinterpret_cast<uint32_t*>(smem + HS * B_SLOT)[i] = 0x3f803f80u;
    fence_async_smem();
    __syncthreads();
    if (wg == 0) {
      int slot = 0, ph = 0;
#pragma unroll 1
      for (int g = 0; g < HG; g++) {
        float acc[96];
#pragma unroll
        for (int i = 0; i < 96; i++) acc[i] = 0.f;
#pragma unroll 1
        for (int st = 0; st < 18; st++) {
          mbar_wait(hb + 8 * slot, ph);
          const uint32_t blo = (((sbd + slot * B_SLOT) >> 4) | ((4096u >> 4) << 16));
          const uint64_t da = desc(((sbd + HS * B_SLOT) >> 4) | (1u << 16), DESC_HI_128);
          wg_fence();
          wgmma_n192<1, false>(acc, da, desc(blo, DESC_HI_128));
          wgmma_n192<1, false>(acc, da, desc(blo + 128, DESC_HI_128));
          wg_commit();
          wg_wait<1>();
          mbar_arrive_if(hb + 8 * (HS + ((slot + HS - 1) & (HS - 1))), tid == 0 && (g | st));
          if (++slot == HS) { slot = 0; ph ^= 1; }
        }
        wg_wait<0>();
        reg_fence(acc);
        if (tid < 4) {
#pragma unroll
          for (int b = 0; b < 24; b++)
            *reinterpret_cast<float2*>(g_cs1 + (blockIdx.x * HG + g) * 192 + b * 8 + tid * 2) = make_float2(acc[b * 4], acc[b * 4 + 1]);
        }
      }
      __syncwarp();
      if (tid == 0) { cnt_arrive(CNT_CS); EV(100); }
    } else if (tid == 128) {
      int slot = 0, ph = 1;
      pace(th0, HW1_START);
#pragma unroll 1
      for (int i = 0; i < HG * 18; i++) {
        mbar_wait(hb + 8 * (HS + slot), ph);
        mbar_expect(hb + 8 * slot, B_SLOT);
        tma3d(sb + slot * B_SLOT, &maps.w1, hb + 8 * slot, 0, (i % 18) * 32, (blockIdx.x * HG + i / 18) * 3);
        if (++slot == HS) { slot = 0; ph ^= 1; }
      }
      constexpr int W2N = DM * DFF * 2 / NHELP / 8192, CN = SEQ * SEQ * 2 * 2 / NHELP / 8192;
#pragma unroll 1
      for (int i = 0; i < W2N; i++) bulk_pf(reinterpret_cast<const char*>(w2) + (size_t)(blockIdx.x * W2N + i) * 8192, 8192);
      EV(101);
      pace(th0, HPF_C_START);
#pragma unroll 1
      for (int i = 0; i < CN; i++)
        bulk_pf(reinterpret_cast<const char*>((blockIdx.x & 1) ? cim : cre) + (size_t)((blockIdx.x >> 1) * CN + i) * 8192, 8192);
      EV(102);
    }
    return;
  }
  const int cta = blockIdx.x - NHELP;
  const int r = cta & 15, p = cta >> 4;
  const int m = p >> 2, q = p & 3;
  const uint32_t bar0 = sb + OFF_BAR;
#define BAR(i) (bar0 + 8u * (uint32_t)(i))

  if ((sb & 0x3FFFFu) != sbd) { asm volatile("st.global.u32 [%0], %1;" ::"l"(0ull), "r"(0) : "memory"); return; }
  uint32_t ticket = 0;
  if (tid == 288) ticket = atomicAdd(&g_cnt[CNT_TICKET * CNT_STRIDE], 1u);
  if (tid < NBAR) {
    const int i = tid;
    int c = 1;
    if (i >= BAR_HF && i < BAR_HF + 9) c = 4;
    if (i == BAR_FOK) c = 7;
    if (i == BAR_ABSTG || i == BAR_ABSTG + 1 || i == BAR_CSD || (i >= BAR_FDONE && i < BAR_FDONE + 17)) c = 4;
    mbar_init(BAR(i), c);
    asm volatile("fence.mbarrier_init.release.cluster;" ::: "memory");
  }
  __syncthreads();

  if (wg == 2) {
    asm volatile("setmaxnreg.dec.sync.aligned.u32 40;");
    if (warp == 0) {
      if (elect_one()) {
        const CUtensorMap* mD = m ? &maps.di : &maps.dr;
        int slot = 0, ph = 1;
#pragma unroll 1
        for (int layer = 0; layer < 2; layer++) {
#pragma unroll 1
          for (int s = 0; s < 18; s++) {
            if (layer == 0 && s <= NB && (s == NB || !(s & 1))) {
#pragma unroll 1
              for (int k = (s + 1) >> 1; k < (s < NB ? (s >> 1) + 1 : 9); k++) {
                mbar_expect(BAR(BAR_XF + k), A_SLOT);
                tma2d(sb + OFF_A + k * A_SLOT, &maps.xin, BAR(BAR_XF + k), k * 64, r * 128);
              }
            }
            mbar_wait(BAR(BAR_BEMPTY + slot), ph);
            const uint32_t fb = BAR(BAR_BFULL + slot);
            mbar_expect(fb, 144 * 64);
            tma3d(sb + OFF_B + slot * B_SLOT, mD, fb, s * 32, q * 48, 0);
            if (++slot == NB) { slot = 0; ph ^= 1; }
          }
#pragma unroll 1
          for (int sg = 0; sg < 18; sg++) {
            const CUtensorMap* mm;
            int row, atom, cw, n, dk = 32;
            if (sg < 6) {
              mm = &maps.abld; row = (layer * 2 + m) * SEQ + q * 512;
              if (sg < 4) { mbar_wait(BAR(BAR_ABOK + sg), layer); row += sg * 128; atom = 0; cw = 1; n = 4; if (sg == 0) EV(6 + layer * 16); }
              else { mbar_wait(BAR(BAR_FOK), layer); atom = (sg - 3) * 3; cw = sg & 1; n = 16; }
            } else if (sg < 13) {
              mm = &maps.w1;
              if (sg < 10) {
                cw = sg & 1;
                const int cut = cw ? G3B_CUT : G3A_CUT;
                atom = p * 9 + cw * 3; row = sg < 8 ? 0 : cut * 32; n = sg < 8 ? cut : 18 - cut;
              } else { cw = 0; atom = p * 9 + 6; row = (12 - sg) * 192; n = 6; }
            } else {
              row = p * 576; cw = sg & 1;
              atom = (sg - 13) * 2;
              if (sg < 17) { mm = &maps.w2; n = 12; dk = 48; }
              else { mm = &maps.w2n; n = 6; dk = 96; }
            }
            const uint32_t fb0 = BAR(BAR_BFULL + cw * NB);
#pragma unroll 1
            for (int i = 0; i < n; i++) {
              mbar_wait(BAR(BAR_BEMPTY + slot), ph);
              mbar_expect(fb0 + 8 * slot, B_SLOT);
              tma3d(sb + OFF_B + slot * B_SLOT, mm, fb0 + 8 * slot, 0, row, atom);
              row += dk;
              if (++slot == NB) { slot = 0; ph ^= 1; }
            }
          }
        }
      }
    } else if (warp == 1) {
      if (lane == 0) {
        const uint32_t ep1 = ticket / NGRID + 1;
        *reinterpret_cast<volatile uint32_t*>(smem + OFF_EPOCH) = ep1;
        mbar_arrive(BAR(BAR_EPOCH));
#pragma unroll 1
        for (int layer = 0; layer < 2; layer++) {
          const int abrow = (layer * 2 + m) * SEQ + r * 128;
          const int abcnt = CNT_AB + ((layer * 2 + m) * 16 + r) * 2;
          const int s0 = (layer * LSTEPS + 15) % NB, s1 = (layer * LSTEPS + 16) % NB, s2 = (layer * LSTEPS + 17) % NB;
          mbar_wait(BAR(BAR_ABSTG), layer);
          EV(3 + layer * 16);
          tma_st2d(&maps.abst, sb + OFF_B + s0 * B_SLOT, q * 48, abrow);
          bulk_commit();
          bulk_wait0();
          EV(4 + layer * 16);
          cnt_arrive(abcnt);
          mbar_arrive(BAR(BAR_BEMPTY + s0));
          EV(5 + layer * 16);
          mbar_wait(BAR(BAR_ABSTG + 1), layer);
          tma_st2d(&maps.abst, sb + OFF_B + s1 * B_SLOT, 192 + q * 48, abrow);
          tma_st2d(&maps.abst, sb + OFF_B + s2 * B_SLOT, 384 + q * 48, abrow);
          bulk_commit();
          bulk_wait0();
          mbar_arrive(BAR(BAR_BEMPTY + s1));
          mbar_arrive(BAR(BAR_BEMPTY + s2));
          cnt_arrive(abcnt + 1);
          release_x(BAR(BAR_FDONE), layer, CNT_X + (layer * 2 * 16 + r) * 9, 9, RELMASK2, EVPH == layer * 2);
#pragma unroll 1
          for (int s = 0; s < 3; s++) {
            mbar_wait(BAR(BAR_RG3C + s), layer);
            mbar_wait(BAR(BAR_RG3B + 6 + s), layer);
            mbar_expect(BAR(BAR_X1F + 9 + s), A_SLOT);
            tma2d(sb + OFF_A + (6 + s) * A_SLOT, &maps.xld, BAR(BAR_X1F + 9 + s), s * 64, r * 128);
          }
#pragma unroll 1
          for (int s = 0; s < 3; s++) mbar_wait(BAR(BAR_X1F + 9 + s), layer);
          cnt_arrive(CNT_G3 + layer * 16 + r);
          cnt_wait(CNT_G3 + layer * 16 + r, ep1 * 8);
          mbar_arrive(BAR(BAR_FOK + 1));
          if (layer == 0) { release_x(BAR(BAR_FDONE + 9), 0, CNT_X + (16 + r) * 9, 8, RELMASK4, EVPH == 1); EV(27); }
        }
      }
    } else if (warp == 2) {
      mbar_wait(BAR(BAR_EPOCH), 0);
      const uint32_t ep1 = *reinterpret_cast<volatile uint32_t*>(smem + OFF_EPOCH);
#pragma unroll 1
      for (int ph4 = 0; ph4 < 4; ph4++) {
        const int layer = ph4 >> 1, second = ph4 & 1;
        if (ph4) {
          const int pl = (ph4 - 1) >> 1, k = min(lane, 8);
          const uint32_t fd = BAR(BAR_FDONE + (second ? 0 : 9));
          const uint32_t fr = BAR(second ? (k < 8 ? BAR_RG2 + k : BAR_RG1 + 8) : BAR_RG4 + k);
          const uint32_t fb = BAR((second ? BAR_X1F : BAR_XF) + k);
          const uint32_t* flag = &g_cnt[(CNT_X + ((ph4 - 1) * 16 + r) * 9 + k) * CNT_STRIDE];
          uint32_t state = lane >= 9 ? 2 : 0;
          mbar_wait(fd, pl);
#pragma unroll 1
          for (uint32_t it = 0;; it++) {
            bool polled = false;
            if (state == 0 && mbar_test(fd + 8 * lane, pl)) {
              uint32_t c;
              asm volatile("ld.acquire.gpu.global.u32 %0, [%1];" : "=r"(c) : "l"(flag) : "memory");
              polled = true;
              if ((int32_t)(c - ep1 * 8) >= 0) {
                fence_async_all();
                state = 1;
                if (!second && k < XEARLY4) { mbar_arrive(BAR(BAR_XOK + k)); state = 2; }
                if (ph4 - 1 == EVPH) EV(64 + lane);
              }
            }
            if (state == 1 && mbar_test(fr, pl)) {
              mbar_expect(fb, A_SLOT);
              tma2d(sb + OFF_A + k * A_SLOT, &maps.xld, fb, k * 64, r * 128);
              state = 2;
              if (ph4 - 1 == EVPH) EV(80 + lane);
            }
            if (__all_sync(0xffffffffu, state == 2)) break;
            if (!__any_sync(0xffffffffu, polled)) __nanosleep(100);
            if (it > 4000000u) { asm volatile("st.global.u32 [%0], %1;" ::"l"(0ull), "r"(0) : "memory"); break; }
          }
        }
        if (!second) {
          int idx = CNT_AB + ((layer * 2 + m) * 16 + q * 4 + (lane & 3)) * 2 + (lane >> 2);
          uint32_t target = ep1 * 4;
          if (lane == 8 || lane == 9) idx = CNT_AB + ((layer * 2 + lane - 8) * 16 + r) * 2;
          if (lane == 10) { idx = CNT_XINIT + r; target = ep1 * 32; }
          uint32_t pend = lane < 11;
          mbar_wait(BAR(BAR_RG1 + 6), layer);
#pragma unroll 1
          for (uint32_t it = 0; __any_sync(0xffffffffu, pend); it++) {
            if (pend) {
              uint32_t v;
              asm volatile("ld.acquire.gpu.global.u32 %0, [%1];" : "=r"(v) : "l"(&g_cnt[idx * CNT_STRIDE]) : "memory");
              if ((int32_t)(v - target) >= 0) {
                fence_async_all();
                mbar_arrive(BAR(lane < 4 ? BAR_ABOK + lane : BAR_FOK));
                pend = 0;
              }
            }
            if (it > 2000000u) { asm volatile("st.global.u32 [%0], %1;" ::"l"(0ull), "r"(0) : "memory"); break; }
          }
        }
      }
    } else {
      const CUtensorMap* mC = m ? &maps.ci : &maps.cr;
      const char* cbase = reinterpret_cast<const char*>((m ? cim : cre) + (size_t)(r * 128 + (lane >> 1)) * SEQ + q * 512) + (lane & 1) * 128;
      asm volatile("prefetch.global.L2 [%0];" ::"l"(cbase));
      const int myrow = r * 128 + p * 16 + (lane >> 1);
      if (lane < 16) {
#pragma unroll
        for (int i = 1; i < 4; i++) g_stat[i * SEQ + r * 128 + p * 16 + lane] = make_ulonglong2(0ull, 0ull);
      }
      auto cload = [&](int k) {
        if (elect_one()) {
          mbar_expect(BAR(BAR_CF + k), A_SLOT);
          tma2d_ef(sb + OFF_A + k * A_SLOT, mC, BAR(BAR_CF + k), q * 512 + k * 64, r * 128);
        }
        __syncwarp();
      };
      mbar_wait(BAR(BAR_XF + CPF_START), 0);
      uint32_t t0 = clock32();
#pragma unroll 1
      for (int i = 1, kc = 0, tc = 0; kc < 8; i++) {
        pace(t0, i * CPF_DT);
        if (i < 32) asm volatile("prefetch.global.L2 [%0];" ::"l"(cbase + (size_t)(i & 7) * 16 * SEQ * 2 + (i >> 3) * 256));
        if (i >= (kc >> 1) * 8 + 7 + CPF_LAG && i >= tc && mbar_test(BAR(BAR_RG1 + kc), 0) && (kc < CEARLY || mbar_test(BAR(BAR_ABOK), 0))) {
          cload(kc);
          kc++;
          tc = i + 1 + (kc & 1);
        }
        if (i > 4000000) { asm volatile("st.global.u32 [%0], %1;" ::"l"(0ull), "r"(0) : "memory"); break; }
      }
      mbar_wait(BAR(BAR_EPOCH), 0);
      const uint32_t ep1 = *reinterpret_cast<volatile uint32_t*>(smem + OFF_EPOCH);
#pragma unroll 1
      for (int ph4 = 1; ph4 < 4; ph4++) {
        const int layer = ph4 >> 1, second = ph4 & 1;
        float s0 = 0.f, q0 = 0.f, s1 = 0.f, q1 = 0.f;
        int kc = 0;
        if (!second) {
          if (elect_one()) {
#pragma unroll 1
            for (int kt = 0; kt < XEARLY4; kt++) {
              mbar_wait(BAR(BAR_XOK + kt), 0);
              mbar_wait(BAR(BAR_RG4 + kt), 0);
              mbar_expect(BAR(BAR_XF + kt), A_SLOT);
              tma2d(sb + OFF_A + kt * A_SLOT, &maps.xld, BAR(BAR_XF + kt), kt * 64, r * 128);
              if (EVPH == 1) EV(80 + kt);
            }
          }
          __syncwarp();
        }
        const int lr = p * 16 + (lane >> 1);
        const uint32_t src = sb + OFF_A + lr * 128 + ((((lane & 1) * 4) ^ (lr & 7)) << 4);
#pragma unroll 1
        for (int k = 0; k < 9; k++) {
          if (ph4 == 1 && k == 6) cnt_wait(CNT_CS, ep1 * NHELP);
          mbar_wait(BAR((second ? BAR_X1F : BAR_XF) + k), layer);
          uint4 v[4];
#pragma unroll
          for (int i = 0; i < 4; i++) v[i] = lds128((src ^ (i << 4)) + k * A_SLOT);
          sum8(v[0], s0, q0); sum8(v[1], s1, q1); sum8(v[2], s0, q0); sum8(v[3], s1, q1);
        }
        s0 += s1; q0 += q1;
        s0 += __shfl_xor_sync(0xffffffffu, s0, 1);
        q0 += __shfl_xor_sync(0xffffffffu, q0, 1);
        if (lane == 0 && !second) EV(8 + layer * 16);
        if (!(lane & 1)) stat_publish(&g_stat[ph4 * SEQ + myrow], s0, q0, ep1);
        if (second) {
          float4 cs[5];
#pragma unroll
          for (int i = 0; i < 5; i++) cs[i] = __ldcg(reinterpret_cast<const float4*>(g_cs1 + p * 576) + min(lane + i * 32, 143));
#pragma unroll
          for (int i = 0; i < 5; i++) reinterpret_cast<float4*>(smem + OFF_CS1)[min(lane + i * 32, 143)] = cs[i];
        }
        if (!second) {
#pragma unroll 1
          for (; kc < CEARLY; kc++) { mbar_wait(BAR(BAR_RG1 + kc), 1); cload(kc); }
        }
        __syncwarp();
        stat_gather(&g_stat[ph4 * SEQ + r * 128 + lane], ep1, reinterpret_cast<float2*>(smem + OFF_STAT) + lane, reinterpret_cast<float*>(smem + OFF_RS) + lane);
        __syncwarp();
        if (lane == 0 && !second) EV(9 + layer * 16);
        mbar_arrive_if(BAR(BAR_STAT + second), lane == 0);
        if (!second) {
#pragma unroll 1
          for (; kc < 8; kc++) {
            if (kc == CEARLY) { mbar_wait(BAR(BAR_ABOK), 1); t0 = clock32(); }
            if (kc > CEARLY) pace(t0, (kc - CEARLY) * CLD_DT);
            mbar_wait(BAR(BAR_RG1 + kc), 1);
            cload(kc);
          }
        }
      }
    }
  } else {
    asm volatile("setmaxnreg.inc.sync.aligned.u32 232;");
    if (wg == 0) TL(0);
    const uint32_t elect = (tid & 127) == 0;
    const uint32_t lane0 = lane == 0;
    if (wg == 1) {
      const int t = tid & 127;
      const int myrow = r * 128 + p * 16 + (t >> 3);
      const uint4* src = reinterpret_cast<const uint4*>(xin + (size_t)myrow * DM) + (t & 7);
      uint4* dst = reinterpret_cast<uint4*>(xout + (size_t)myrow * DM) + (t & 7);
      uint4 v[9], d[9];
#pragma unroll
      for (int i = 0; i < 9; i++) v[i] = __ldg(src + i * 8);
      const int n = r * 9 + min(t >> 3, 8);
      const uint4* dsrc = reinterpret_cast<const uint4*>((m ? dim : dre) + (size_t)((n / 48) * 192 + q * 48 + n % 48) * DM) + (t & 7);
#pragma unroll
      for (int i = 0; i < 9; i++) d[i] = __ldg(dsrc + i * 8);
      float s = 0.f, qq = 0.f, sd = 0.f;
#pragma unroll
      for (int i = 0; i < 9; i++) {
        sum8(v[i], s, qq);
        sd += ((bf_lo(d[i].x) + bf_hi(d[i].x)) + (bf_lo(d[i].y) + bf_hi(d[i].y))) + ((bf_lo(d[i].z) + bf_hi(d[i].z)) + (bf_lo(d[i].w) + bf_hi(d[i].w)));
      }
#pragma unroll
      for (int o = 1; o < 8; o <<= 1) {
        s += __shfl_xor_sync(0xffffffffu, s, o);
        qq += __shfl_xor_sync(0xffffffffu, qq, o);
        sd += __shfl_xor_sync(0xffffffffu, sd, o);
      }
      mbar_wait(BAR(BAR_EPOCH), 0);
      const uint32_t ep1 = *reinterpret_cast<volatile uint32_t*>(smem + OFF_EPOCH);
      if ((t & 7) == 0) {
        stat_publish(&g_stat[myrow], s, qq, ep1);
        if (t < 72) asm volatile("st.relaxed.gpu.global.u64 [%0], %1;" ::"l"(&g_csd[p * 144 + n]), "l"(((unsigned long long)ep1 << 32) | __float_as_uint(sd)) : "memory");
      }
#pragma unroll
      for (int i = 0; i < 9; i++) dst[i * 8] = v[i];
      if (t < 72) {
        unsigned long long a, b;
#pragma unroll 1
        for (uint32_t it = 0;; it++) {
          asm volatile("ld.relaxed.gpu.global.v2.u64 {%0, %1}, [%2];" : "=l"(a), "=l"(b) : "l"(&g_csd[p * 144 + t * 2]) : "memory");
          if ((uint32_t)(a >> 32) == ep1 && (uint32_t)(b >> 32) == ep1) break;
          if (it > 2000000u) { asm volatile("st.global.u32 [%0], %1;" ::"l"(0ull), "r"(0) : "memory"); break; }
        }
        reinterpret_cast<float2*>(smem + OFF_CSD)[t] = make_float2(__uint_as_float((uint32_t)a), __uint_as_float((uint32_t)b));
      }
      if (warp == 3) {
        stat_gather(&g_stat[r * 128 + lane], ep1, reinterpret_cast<float2*>(smem + OFF_STAT) + lane, reinterpret_cast<float*>(smem + OFF_RS) + lane);
        __syncwarp();
        mbar_arrive_if(BAR(BAR_STAT), lane0);
      }
      __syncwarp();
      EVE(10);
      mbar_arrive_if(BAR(BAR_CSD), lane0);
      if (lane == 0) cnt_arrive(CNT_XINIT + r);
      asm volatile("bar.sync 2, 128;" ::: "memory");
    }

    const int srow = (lane & 7) + ((lane >> 3) & 1) * 8;
    const int schunk = lane >> 4;
    const int frow = warp * 16 + (lane >> 2);
    const uint32_t bfull = BAR(BAR_BFULL + wg * NB);
    constexpr uint32_t alo0 = ((sbd + OFF_A) >> 4) | (1u << 16);
    float rs[4];
    uint32_t bph = 0;

#pragma unroll 1
    for (int layer = 0; layer < 2; layer++) {
#pragma unroll
      for (int i = 0; i < 4; i++) rs[i] = 1.f;
      auto flush = [&](auto& acc0, auto& acc1, auto na, int pi, int atom0) {
        constexpr int NA = decltype(na)::value;
        const int ffn = pi >= 7;
        const uint32_t fdone = BAR(BAR_FDONE + ffn * 9 + atom0);
        mbar_wait(BAR(BAR_FOK + ffn), layer);
        constexpr int HOFF = 2048;
        if (atom0) mbar_wait(fdone - 8, layer);
        const uint32_t stg = sb + OFF_STG + warp * 4096;
        const uint32_t sad = stg + srow * 128;
        const uint32_t dt = pi == 10 ? FLUSH_DT_D : (pi == 3 ? FLUSH_DT_C : FLUSH_DT);
        uint32_t tn = clock32() + warp * (dt * STAGGER / 4);
#pragma unroll
        for (int n = 0; n < 2 * NA; n++) {
          uint32_t w[16];
#pragma unroll
          for (int j = 0; j < 16; j++) {
            const int o = (n >> 1) * 32 + j * 2;
            if (NA == 3) {
              w[j] = (n & 1) ? pk(acc1[o], acc1[o + 1]) : pk(acc0[o], acc0[o + 1]);
            } else {
              const float f = rs[(n & 1) * 2 + (j & 1)];
              w[j] = (n & 1) ? pk(acc1[o] * f, acc1[o + 1] * f) : pk(acc0[o] * f, acc0[o + 1] * f);
            }
          }
#pragma unroll
          for (int j = 0; j < 4; j++)
            stsm4(sad + (n & 1) * HOFF + (((j * 2 + schunk) ^ (srow & 7)) << 4), w[j * 4], w[j * 4 + 1], w[j * 4 + 2], w[j * 4 + 3]);
          fence_async_smem();
          if (n > FRONT) tn += dt;
          spin_until(tn);
          __syncwarp();
          if (elect_one()) {
            tma_red2d(&maps.xred, stg + (n & 1) * HOFF, (atom0 + (n >> 1)) * 64, r * 128 + (n & 1) * 64 + warp * 16);
            bulk_commit();
            if (n == 2 * NA - 1) {
              bulk_wait0();
              mbar_arrive(fdone + 8 * (NA - 1));
            } else if (n) {
              asm volatile("cp.async.bulk.wait_group 1;" ::: "memory");
              if (!(n & 1)) mbar_arrive(fdone + 8 * ((n >> 1) - 1));
            }
          }
          __syncwarp();
        }
      };
      if (wg == 0) {
        float acc0[72], acc1[72];
        constexpr uint32_t blo0 = ((sbd + OFF_B) >> 4) | (1u << 16);
        int slot = (layer * LSTEPS) % NB, pslot = 0;
        uint32_t ready = 0;
        auto step = [&](int s, auto first) {
          constexpr bool F = decltype(first)::value;
          const int kt = s >> 1;
          if (!ready) {
            mbar_wait(BAR(BAR_XF + kt), layer);
            mbar_wait(bfull + 8 * slot, (bph >> slot) & 1);
            if (F && layer) mbar_wait(BAR(BAR_GO + 13), 0);
          }
          bph ^= 1u << slot;
          if (F) TL(1 + layer * 36);
          const uint32_t alo = alo0 + kt * (A_SLOT >> 4) + (s & 1) * 4;
          const uint32_t blo = blo0 + slot * (B_SLOT >> 4);
          wg_fence();
          wgmma_n144<0, F>(acc0, desc(alo, DESC_HI_128), desc(blo, DESC_HI_64));
          wgmma_n144<0, F>(acc1, desc(alo + 512, DESC_HI_128), desc(blo, DESC_HI_64));
          wgmma_n144<0, false>(acc0, desc(alo + 2, DESC_HI_128), desc(blo + 2, DESC_HI_64));
          wgmma_n144<0, false>(acc1, desc(alo + 514, DESC_HI_128), desc(blo + 2, DESC_HI_64));
          wg_commit();
          const int cslot = slot;
          if (++slot == NB) slot = 0;
          ready = mbar_test(BAR(BAR_XF + ((s + 1) >> 1)), layer) & mbar_test(bfull + 8 * slot, (bph >> slot) & 1);
          if (!F) {
            wg_wait<1>();
            mbar_arrive_if(BAR(BAR_BEMPTY + pslot), elect && s < 16);
            mbar_arrive_if(BAR(BAR_RG1 - 1 + kt), elect && !(s & 1));
          }
          pslot = cslot;
        };
        step(0, TrueT{});
#pragma unroll 1
        for (int s = 1; s < 18; s++) step(s, FalseT{});
        mbar_arrive_if(BAR(BAR_GO), elect);
        mbar_wait(BAR(BAR_CSD), 0);
        float2 cd[18];
#pragma unroll
        for (int i = 0; i < 18; i++) cd[i] = lds64f(sb + OFF_CSD + (i * 8 + (lane & 3) * 2) * 4);
        wg_wait<0>();
        reg_fence(acc0); reg_fence(acc1);
        TL(2 + layer * 36);
        mbar_arrive_if(BAR(BAR_RG1 + 8), elect);
        asm volatile("bar.sync %0, 128;" ::"r"(1 + wg) : "memory");
        mbar_wait(BAR(BAR_STAT), layer);
        EVE(1 + layer * 16);
        const float sg = m ? -1.f : 1.f;
        float2 st[4];
#pragma unroll
        for (int i = 0; i < 4; i++) {
          st[i] = lds64f(sb + OFF_STAT + (frow + (i & 1) * 8 + (i >> 1) * 64) * 8);
          st[i].x *= sg;
        }
        const uint32_t stg = sb + OFF_B + (warp * 16 + srow) * 96 + schunk * 16;
#pragma unroll
        for (int b2 = 0; b2 < 9; b2++) {
          const float2 c0 = cd[b2 * 2], c1 = cd[b2 * 2 + 1];
          const uint32_t ad = stg + ((layer * LSTEPS + 15 + b2 / 3) % NB) * B_SLOT + (b2 % 3) * 32;
          const int o = b2 * 8;
          stsm4(ad,
                pk(fmaf(c0.x, st[0].y, acc0[o]) * st[0].x, fmaf(c0.y, st[0].y, acc0[o + 1]) * st[0].x),
                pk(fmaf(c0.x, st[1].y, acc0[o + 2]) * st[1].x, fmaf(c0.y, st[1].y, acc0[o + 3]) * st[1].x),
                pk(fmaf(c1.x, st[0].y, acc0[o + 4]) * st[0].x, fmaf(c1.y, st[0].y, acc0[o + 5]) * st[0].x),
                pk(fmaf(c1.x, st[1].y, acc0[o + 6]) * st[1].x, fmaf(c1.y, st[1].y, acc0[o + 7]) * st[1].x));
          stsm4(ad + 64 * 96,
                pk(fmaf(c0.x, st[2].y, acc1[o]) * st[2].x, fmaf(c0.y, st[2].y, acc1[o + 1]) * st[2].x),
                pk(fmaf(c0.x, st[3].y, acc1[o + 2]) * st[3].x, fmaf(c0.y, st[3].y, acc1[o + 3]) * st[3].x),
                pk(fmaf(c1.x, st[2].y, acc1[o + 4]) * st[2].x, fmaf(c1.y, st[2].y, acc1[o + 5]) * st[2].x),
                pk(fmaf(c1.x, st[3].y, acc1[o + 6]) * st[3].x, fmaf(c1.y, st[3].y, acc1[o + 7]) * st[3].x));
          if (b2 == 2 || b2 == 8) {
            fence_async_smem();
            __syncwarp();
            mbar_arrive_if(BAR(BAR_ABSTG + (b2 == 8)), lane0);
          }
        }
        TL(3 + layer * 36);
      }
#pragma unroll 1
      for (int pi = 2 - wg; pi < 12; pi += 2) {
        if (pi < 7) {
          float acc0[96], acc1[96];
          int atom0;
          int nsteps = 18, seq, cut = 64, gap = 0, fbar, rbar = BAR_RNONE, sgm = pi;
          if (pi < 4) { atom0 = (pi - 1) * 3; nsteps = 16; seq = 2 + pi * 16; fbar = BAR_CF; if (pi == 3) rbar = BAR_RG2; }
          else if (pi == 4) { atom0 = 0; seq = 66; cut = G3A_CUT; gap = G3B_CUT; fbar = BAR_X1F; }
          else if (pi == 5) { atom0 = 3; seq = 66 + G3A_CUT; cut = G3B_CUT; gap = 18 - G3A_CUT; fbar = BAR_X1F; rbar = BAR_RG3B; }
          else { atom0 = 6; seq = 102; fbar = BAR_X1F + 3; rbar = BAR_RG3C; sgm = 8; }
          constexpr uint32_t blo0 = ((sbd + OFF_B) >> 4) | ((4096u >> 4) << 16);
          int slot = (seq + layer * LSTEPS) % NB, pslot = 0;
          int aslot = (pi == 6) ? 6 : 0;
          uint32_t ready = 0;
          auto step = [&](int s, auto first) {
            constexpr bool F = decltype(first)::value;
            const int kt = s >> 1;
            if (!ready) {
              mbar_wait(BAR(fbar + kt), layer);
              mbar_wait(bfull + 8 * slot, (bph >> slot) & 1);
              if (F || s == cut) mbar_wait(BAR(BAR_GO - 1 + sgm), layer);
            }
            bph ^= 1u << slot;
            if (F) TL(1 + pi * 3 + layer * 36);
            const uint32_t alo = alo0 + aslot * (A_SLOT >> 4) + (s & 1) * 4;
            const uint32_t blo = blo0 + slot * (B_SLOT >> 4);
            wg_fence();
            wgmma_n192<1, F>(acc0, desc(alo, DESC_HI_128), desc(blo, DESC_HI_128));
            wgmma_n192<1, F>(acc1, desc(alo + 512, DESC_HI_128), desc(blo, DESC_HI_128));
            wgmma_n192<1, false>(acc0, desc(alo + 2, DESC_HI_128), desc(blo + 128, DESC_HI_128));
            wgmma_n192<1, false>(acc1, desc(alo + 514, DESC_HI_128), desc(blo + 128, DESC_HI_128));
            wg_commit();
            const int cslot = slot;
            if (++slot == NB) slot = 0;
            if (s & 1) { if (++aslot == 9) aslot = 3; }
            if (!F && (s + 1 == cut || s + 1 == nsteps)) {
              mbar_arrive_if(BAR(BAR_GO + sgm), elect);
              sgm += 2;
              slot = (slot + gap) % NB;
              ready = 0;
              wg_wait<1>();
              mbar_arrive_if(BAR(BAR_BEMPTY + pslot), elect);
              wg_wait<0>();
              mbar_arrive_if(BAR(BAR_BEMPTY + cslot), elect);
              mbar_arrive_if(BAR(rbar + kt), elect);
            } else {
              ready = mbar_test(BAR(fbar + ((s + 1) >> 1)), layer) & mbar_test(bfull + 8 * slot, (bph >> slot) & 1);
              if (!F) {
                wg_wait<1>();
                const uint32_t rel = elect && s != cut;
                mbar_arrive_if(BAR(BAR_BEMPTY + pslot), rel);
                mbar_arrive_if(BAR(rbar - 1 + kt), rel && !(s & 1));
              }
            }
            pslot = cslot;
          };
          step(0, TrueT{});
#pragma unroll 1
          for (int s = 1; s < nsteps; s++) step(s, FalseT{});
        wg_wait<0>();
        reg_fence(acc0); reg_fence(acc1);
        TL(2 + pi * 3 + layer * 36);
        if (pi >= 4 && pi <= 6) {
          mbar_wait(BAR(BAR_STAT + 1), layer);
          if (pi == 4) mbar_wait(BAR(BAR_RG3B + 2), layer);
          asm volatile("bar.sync %0, 128;" ::"r"(1 + wg) : "memory");
          float2 st[4];
#pragma unroll
          for (int i = 0; i < 4; i++) st[i] = lds64f(sb + OFF_STAT + (frow + (i & 1) * 8 + (i >> 1) * 64) * 8);
#pragma unroll
          for (int i = 0; i < 4; i++) rs[i] = st[i].x;
          const uint32_t cs = sb + OFF_CS1 + (atom0 * 64 + (lane & 3) * 2) * 4;
          const uint32_t dst = sb + OFF_A + atom0 * A_SLOT + (warp * 16 + srow) * 128;
          float2 cn[2][2];
          cn[0][0] = lds64f(cs); cn[0][1] = lds64f(cs + 32); cn[1][0] = lds64f(cs + 64); cn[1][1] = lds64f(cs + 96);
#pragma unroll
          for (int b2 = 0; b2 < 12; b2++) {
            if ((b2 & 3) == 0 && pi == 5) mbar_wait(BAR(BAR_RG3C + 3 + (b2 >> 2)), layer);
            const float2 c0 = cn[b2 & 1][0], c1 = cn[b2 & 1][1];
            if (b2 + 2 < 12) { cn[b2 & 1][0] = lds64f(cs + (b2 + 2) * 64); cn[b2 & 1][1] = lds64f(cs + (b2 + 2) * 64 + 32); }
            const uint32_t ad = dst + (b2 >> 2) * A_SLOT + ((((b2 & 3) * 2 + schunk) ^ (srow & 7)) << 4);
            const int o = b2 * 8;
            stsm4(ad,
                  pk_relu(fmaf(c0.x, st[0].y, acc0[o]), fmaf(c0.y, st[0].y, acc0[o + 1])),
                  pk_relu(fmaf(c0.x, st[1].y, acc0[o + 2]), fmaf(c0.y, st[1].y, acc0[o + 3])),
                  pk_relu(fmaf(c1.x, st[0].y, acc0[o + 4]), fmaf(c1.y, st[0].y, acc0[o + 5])),
                  pk_relu(fmaf(c1.x, st[1].y, acc0[o + 6]), fmaf(c1.y, st[1].y, acc0[o + 7])));
            stsm4(ad + 8192,
                  pk_relu(fmaf(c0.x, st[2].y, acc1[o]), fmaf(c0.y, st[2].y, acc1[o + 1])),
                  pk_relu(fmaf(c0.x, st[3].y, acc1[o + 2]), fmaf(c0.y, st[3].y, acc1[o + 3])),
                  pk_relu(fmaf(c1.x, st[2].y, acc1[o + 4]), fmaf(c1.y, st[2].y, acc1[o + 5])),
                  pk_relu(fmaf(c1.x, st[3].y, acc1[o + 6]), fmaf(c1.y, st[3].y, acc1[o + 7])));
            if ((b2 & 3) == 3) {
              fence_async_smem();
              __syncwarp();
              mbar_arrive_if(BAR(BAR_HF + atom0 + (b2 >> 2)), lane0);
            }
          }
        } else {
          flush(acc0, acc1, IntT<3>{}, pi, atom0);
        }
        } else {
          auto hpass = [&](auto na) {
            constexpr int NA = decltype(na)::value, KU = 6 / NA, NS = 36 / KU;
            float a0[64], a1[NA == 2 ? 64 : 1];
            constexpr uint32_t blo0 = ((sbd + OFF_B) >> 4) | ((6144u >> 4) << 16);
            int slot = (36 + pi * 12 + layer * LSTEPS) % NB, pslot = 0;
            uint32_t ready = 0;
            auto step = [&](int s, auto first) {
              constexpr bool F = decltype(first)::value;
              if (!ready) {
                if (NA == 2) mbar_wait(BAR(BAR_HF + ((s * KU + KU - 1) >> 2)), layer);
                mbar_wait(bfull + 8 * slot, (bph >> slot) & 1);
                if (F) mbar_wait(BAR(BAR_GO + 1 + pi), layer);
              }
              bph ^= 1u << slot;
              if (F) TL(1 + pi * 3 + layer * 36);
              const uint32_t blo = blo0 + slot * (B_SLOT >> 4);
              wg_fence();
#pragma unroll
              for (int j = 0; j < KU; j++) {
                const int u = s * KU + j;
                const uint64_t da0 = desc(alo0 + (u >> 2) * (A_SLOT >> 4) + (u & 3) * 2, DESC_HI_128);
                const uint64_t da1 = desc(alo0 + (u >> 2) * (A_SLOT >> 4) + (u & 3) * 2 + 512, DESC_HI_128);
                const uint64_t db = desc(blo + j * 128, DESC_HI_128);
                if constexpr (NA == 2) {
                  if (F && j == 0) { wgmma_n128<1, true>(a0, da0, db); wgmma_n128<1, true>(a1, da1, db); }
                  else { wgmma_n128<1, false>(a0, da0, db); wgmma_n128<1, false>(a1, da1, db); }
                } else {
                  if (F && j == 0) wgmma_n128<0, true, 1>(a0, db, da0);
                  else wgmma_n128<0, false, 1>(a0, db, da0);
                }
              }
              wg_commit();
              const int cslot = slot;
              if (++slot == NB) slot = 0;
              mbar_arrive_if(BAR(BAR_GO + 2 + pi), elect && s == NS - 1);
              ready = mbar_test(bfull + 8 * slot, (bph >> slot) & 1);
              if (NA == 2) ready &= mbar_test(BAR(BAR_HF + ((s * KU + 2 * KU - 1) >> 2)), layer);
              if (!F) {
                wg_wait<1>();
                mbar_arrive_if(BAR(BAR_BEMPTY + pslot), elect);
                if (NA == 1) {
                  mbar_arrive_if(BAR(BAR_RG4 - 1 + ((6 * s) >> 2)), elect);
                  mbar_arrive_if(BAR(BAR_RG4 - 2 + ((6 * s) >> 2)), elect && !(s & 1));
                }
              }
              pslot = cslot;
            };
            float2 rsv[NA == 1 ? 16 : 1];
            if constexpr (NA == 1) {
#pragma unroll
              for (int i = 0; i < 16; i++) rsv[i] = lds64f(sb + OFF_RS + (i * 8 + (lane & 3) * 2) * 4);
            }
            step(0, TrueT{});
#pragma unroll 1
            for (int s = 1; s < NS; s++) step(s, FalseT{});
            wg_wait<0>();
            mbar_arrive_if(BAR(BAR_BEMPTY + pslot), elect);
            if (NA == 1) { mbar_arrive_if(BAR(BAR_RG4 + 7), elect); mbar_arrive_if(BAR(BAR_RG4 + 8), elect); }
            reg_fence(a0);
            TL(2 + pi * 3 + layer * 36);
            if constexpr (NA == 2) {
              reg_fence(a1);
              flush(a0, a1, na, pi, (pi - 7) * 2);
            } else {
              asm volatile("bar.sync %0, 128;" ::"r"(1 + wg) : "memory");
              const uint32_t tb = sb + OFF_A + 8 * A_SLOT;
              const uint32_t ad = tb + ((lane >> 4) * 8 + (lane & 7)) * 128 + (((warp * 2 + ((lane >> 3) & 1)) ^ (lane & 7)) << 4);
#pragma unroll
              for (int b2 = 0; b2 < 8; b2++) {
                const float2 f0 = rsv[b2 * 2], f1 = rsv[b2 * 2 + 1];
                const int o = b2 * 8;
                asm volatile("stmatrix.sync.aligned.m8n8.x4.trans.shared.b16 [%0], {%1,%2,%3,%4};" ::"r"(ad + b2 * 2048),
                             "r"(pk(a0[o] * f0.x, a0[o + 1] * f0.y)), "r"(pk(a0[o + 2] * f0.x, a0[o + 3] * f0.y)),
                             "r"(pk(a0[o + 4] * f1.x, a0[o + 5] * f1.y)), "r"(pk(a0[o + 6] * f1.x, a0[o + 7] * f1.y)));
              }
              fence_async_smem();
              asm volatile("bar.sync %0, 128;" ::"r"(1 + wg) : "memory");
              if (warp == 0 && elect_one()) {
                tma_red2d(&maps.xld, tb, 512, r * 128);
                bulk_commit();
                bulk_wait0();
                mbar_arrive(BAR(BAR_FDONE + 17));
                if (EVPH == 1 && layer == 0) EV(40);
                if (layer == 0) cnt_arrive(CNT_X + (16 + r) * 9 + 8);
                if (EVPH == 1 && layer == 0) EV(56);
              }
              __syncwarp();
            }
          };
          if (pi < 11) hpass(IntT<2>{}); else hpass(IntT<1>{});
        }
        TL(3 + pi * 3 + layer * 36);
      }
    }
  }
#undef BAR
}

typedef CUresult (*EncodeFn)(CUtensorMap*, CUtensorMapDataType, cuuint32_t, void*, const cuuint64_t*, const cuuint64_t*, const cuuint32_t*,
                             const cuuint32_t*, CUtensorMapInterleave, CUtensorMapSwizzle, CUtensorMapL2promotion, CUtensorMapFloatOOBfill);

void make2d(EncodeFn enc, CUtensorMap* m, const void* ptr, uint64_t inner, uint64_t outer, uint32_t bi, uint32_t bo, CUtensorMapSwizzle sw) {
  cuuint64_t d[2] = {inner, outer};
  cuuint64_t s[1] = {inner * 2};
  cuuint32_t b[2] = {bi, bo}, e[2] = {1, 1};
  enc(m, CU_TENSOR_MAP_DATA_TYPE_BFLOAT16, 2, const_cast<void*>(ptr), d, s, b, e, CU_TENSOR_MAP_INTERLEAVE_NONE, sw,
      CU_TENSOR_MAP_L2_PROMOTION_L2_128B, CU_TENSOR_MAP_FLOAT_OOB_FILL_NONE);
}
void make3d(EncodeFn enc, CUtensorMap* m, const void* ptr, uint64_t d0, uint64_t d1, uint64_t d2, uint64_t s1, uint64_t s2,
            uint32_t b0, uint32_t b1, uint32_t b2, CUtensorMapSwizzle sw) {
  cuuint64_t d[3] = {d0, d1, d2};
  cuuint64_t s[2] = {s1, s2};
  cuuint32_t b[3] = {b0, b1, b2}, e[3] = {1, 1, 1};
  enc(m, CU_TENSOR_MAP_DATA_TYPE_BFLOAT16, 3, const_cast<void*>(ptr), d, s, b, e, CU_TENSOR_MAP_INTERLEAVE_NONE, sw,
      CU_TENSOR_MAP_L2_PROMOTION_L2_128B, CU_TENSOR_MAP_FLOAT_OOB_FILL_NONE);
}

}

extern "C" void kernel_launch(void* const* d_in, const int* in_sizes, int n_in, void* d_out, int out_size) {
  (void)in_sizes; (void)n_in; (void)out_size;
  const __nv_bfloat16* x = (const __nv_bfloat16*)d_in[0];
  const __nv_bfloat16* cr = (const __nv_bfloat16*)d_in[1];
  const __nv_bfloat16* ci = (const __nv_bfloat16*)d_in[2];
  const __nv_bfloat16* dr = (const __nv_bfloat16*)d_in[3];
  const __nv_bfloat16* di = (const __nv_bfloat16*)d_in[4];
  const __nv_bfloat16* w1 = (const __nv_bfloat16*)d_in[6];
  const __nv_bfloat16* w2 = (const __nv_bfloat16*)d_in[7];
  __nv_bfloat16* out = (__nv_bfloat16*)d_out;

  void* fn = nullptr;
  cudaDriverEntryPointQueryResult qr;
  cudaGetDriverEntryPoint("cuTensorMapEncodeTiled", &fn, cudaEnableDefault, &qr);
  EncodeFn enc = (EncodeFn)fn;
  void* ab = nullptr;
  cudaGetSymbolAddress(&ab, g_ab);

  Maps maps;
  make2d(enc, &maps.xin, x, DM, SEQ, 64, 128, CU_TENSOR_MAP_SWIZZLE_128B);
  make2d(enc, &maps.xld, out, DM, SEQ, 64, 128, CU_TENSOR_MAP_SWIZZLE_128B);
  make2d(enc, &maps.xred, out, DM, SEQ, 64, 16, CU_TENSOR_MAP_SWIZZLE_128B);
  make2d(enc, &maps.cr, cr, SEQ, SEQ, 64, 128, CU_TENSOR_MAP_SWIZZLE_128B);
  make2d(enc, &maps.ci, ci, SEQ, SEQ, 64, 128, CU_TENSOR_MAP_SWIZZLE_128B);
  make3d(enc, &maps.dr, dr, DM, 192, 3, DM * 2, 192 * DM * 2, 32, 48, 3, CU_TENSOR_MAP_SWIZZLE_64B);
  make3d(enc, &maps.di, di, DM, 192, 3, DM * 2, 192 * DM * 2, 32, 48, 3, CU_TENSOR_MAP_SWIZZLE_64B);
  make3d(enc, &maps.abld, ab, 64, 4 * SEQ, DM / 64, DM * 2, 128, 64, 32, 3, CU_TENSOR_MAP_SWIZZLE_128B);
  make2d(enc, &maps.abst, ab, DM, 4 * SEQ, 48, 128, CU_TENSOR_MAP_SWIZZLE_NONE);
  make3d(enc, &maps.w1, w1, 64, DM, DFF / 64, DFF * 2, 128, 64, 32, 3, CU_TENSOR_MAP_SWIZZLE_128B);
  make3d(enc, &maps.w2, w2, 64, DFF, DM / 64, DM * 2, 128, 64, 48, 2, CU_TENSOR_MAP_SWIZZLE_128B);
  make3d(enc, &maps.w2n, w2, 64, DFF, DM / 64, DM * 2, 128, 64, 96, 1, CU_TENSOR_MAP_SWIZZLE_128B);

  cudaFuncSetAttribute(fnet_ffn_kernel, cudaFuncAttributeMaxDynamicSharedMemorySize, SMEM_BYTES);
  cudaLaunchConfig_t cfg = {};
  cfg.gridDim = dim3(NGRID);
  cfg.blockDim = dim3(384);
  cfg.dynamicSmemBytes = SMEM_BYTES;
  cfg.stream = cudaStreamPerThread;
  cudaLaunchAttribute at[1];
  at[0].id = cudaLaunchAttributeClusterDimension;
  at[0].val.clusterDim.x = CLUSTER; at[0].val.clusterDim.y = 1; at[0].val.clusterDim.z = 1;
  cfg.attrs = at;
  cfg.numAttrs = 1;
  cudaLaunchKernelEx(&cfg, fnet_ffn_kernel, maps, x, cr, ci, dr, di, w1, w2, out);
}
```

```cpp
#include <cuda_runtime.h>
#include <cuda_bf16.h>
#include <cuda.h>
#include <stdint.h>

namespace {

constexpr int SEQ = 2048, DM = 576, DFF = 4608;
constexpr int NHELP = 4, NWORK = 128, NGRID = NHELP + NWORK;

constexpr int A_SLOT = 16384, B_SLOT = 12288, NB = 5, LSTEPS = 161, D_SLOT = 18432;
constexpr int OFF_A = 0;
constexpr int OFF_B = 9 * A_SLOT;
constexpr int OFF_STG = OFF_B + NB * B_SLOT;
constexpr int OFF_CS1 = OFF_STG + 12288;
constexpr int OFF_CSD = OFF_STG + 16384;
constexpr int OFF_EPOCH = OFF_CSD + 576;
constexpr int OFF_RS = OFF_CSD + 640;
constexpr int OFF_BAR = OFF_RS + 512;
constexpr int SMEM_BYTES = 232448;

constexpr int BAR_HF = 0  , BAR_ABSTG = 9  , BAR_FDONE = 11  ,
              BAR_BFULL = 32  , BAR_BEMPTY = 42  , BAR_CF = 47  , BAR_X1F = 55  ,
              BAR_RG1 = 68, BAR_RG2 = 77, BAR_RG3B = 86, BAR_RG3C = 95, BAR_RG4 = 104, BAR_RNONE = 113  ,
              BAR_STAT = 122  , BAR_FOK = 124  , BAR_EPOCH = 126, BAR_CSD = 127,
              BAR_XF = 128  , BAR_DF = 137  , BAR_ABOK = 146  , BAR_GO = 150  , BAR_XOK = 166  , BAR_SENT = 175, BAR_RSOK = 176, BAR_CSOK = 177, BAR_A7 = 178, BAR_S6 = 179, NBAR = 192;
constexpr int OFF_MEAN = OFF_BAR + NBAR * 8;
static_assert(OFF_MEAN + 512 <= SMEM_BYTES, "smem");

constexpr int CNT_STRIDE = 32;
constexpr int CNT_AB = 0;
constexpr int CNT_X = 128;
constexpr int CNT_XINIT = CNT_X + 432;
constexpr int CNT_G3 = CNT_XINIT + 16;
constexpr int CNT_CS = CNT_G3 + 32;
constexpr int CNT_TICKET = CNT_CS + 1;
constexpr int NCNT = CNT_TICKET + 1;

__device__ uint32_t g_cnt[NCNT * CNT_STRIDE];
__device__ __nv_bfloat16 g_ab[2 * 2 * SEQ * DM];
__device__ float g_cs1[DFF];
__device__ __align__(16) float g_rsum[2 * SEQ];
__device__ __align__(16) unsigned long long g_csd[8 * 144];
__device__ ulonglong2 g_stat[3 * SEQ];
#define TL(i)
#define EV(i)
#define EVE(i)

template <int V> struct IntT { static constexpr int value = V; };
struct TrueT { static constexpr bool value = true; };
struct FalseT { static constexpr bool value = false; };

struct Maps {
  CUtensorMap xin, xld, xred, cr, ci, dr, di, abld, abst, w1, w2, w2n;
};

template<int TB, bool FIRST, int TA = 0> __device__ __forceinline__ void wgmma_n128(float (&d)[64], uint64_t da, uint64_t db){
  if (FIRST) {
    asm volatile("wgmma.mma_async.sync.aligned.m64n128k16.f32.bf16.bf16 {%0, %1, %2, %3, %4, %5, %6, %7, %8, %9, %10, %11, %12, %13, %14, %15, %16, %17, %18, %19, %20, %21, %22, %23, %24, %25, %26, %27, %28, %29, %30, %31, %32, %33, %34, %35, %36, %37, %38, %39, %40, %41, %42, %43, %44, %45, %46, %47, %48, %49, %50, %51, %52, %53, %54, %55, %56, %57, %58, %59, %60, %61, %62, %63}, %64, %65, 0, 1, 1, %67, %66;"
     : "=f"(d[0]), "=f"(d[1]), "=f"(d[2]), "=f"(d[3]), "=f"(d[4]), "=f"(d[5]), "=f"(d[6]), "=f"(d[7]), "=f"(d[8]), "=f"(d[9]), "=f"(d[10]), "=f"(d[11]), "=f"(d[12]), "=f"(d[13]), "=f"(d[14]), "=f"(d[15]), "=f"(d[16]), "=f"(d[17]), "=f"(d[18]), "=f"(d[19]), "=f"(d[20]), "=f"(d[21]), "=f"(d[22]), "=f"(d[23]), "=f"(d[24]), "=f"(d[25]), "=f"(d[26]), "=f"(d[27]), "=f"(d[28]), "=f"(d[29]), "=f"(d[30]), "=f"(d[31]), "=f"(d[32]), "=f"(d[33]), "=f"(d[34]), "=f"(d[35]), "=f"(d[36]), "=f"(d[37]), "=f"(d[38]), "=f"(d[39]), "=f"(d[40]), "=f"(d[41]), "=f"(d[42]), "=f"(d[43]), "=f"(d[44]), "=f"(d[45]), "=f"(d[46]), "=f"(d[47]), "=f"(d[48]), "=f"(d[49]), "=f"(d[50]), "=f"(d[51]), "=f"(d[52]), "=f"(d[53]), "=f"(d[54]), "=f"(d[55]), "=f"(d[56]), "=f"(d[57]), "=f"(d[58]), "=f"(d[59]), "=f"(d[60]), "=f"(d[61]), "=f"(d[62]), "=f"(d[63])
     : "l"(da), "l"(db), "n"(TB), "n"(TA));
  } else {
    asm volatile("wgmma.mma_async.sync.aligned.m64n128k16.f32.bf16.bf16 {%0, %1, %2, %3, %4, %5, %6, %7, %8, %9, %10, %11, %12, %13, %14, %15, %16, %17, %18, %19, %20, %21, %22, %23, %24, %25, %26, %27, %28, %29, %30, %31, %32, %33, %34, %35, %36, %37, %38, %39, %40, %41, %42, %43, %44, %45, %46, %47, %48, %49, %50, %51, %52, %53, %54, %55, %56, %57, %58, %59, %60, %61, %62, %63}, %64, %65, 1, 1, 1, %67, %66;"
     : "+f"(d[0]), "+f"(d[1]), "+f"(d[2]), "+f"(d[3]), "+f"(d[4]), "+f"(d[5]), "+f"(d[6]), "+f"(d[7]), "+f"(d[8]), "+f"(d[9]), "+f"(d[10]), "+f"(d[11]), "+f"(d[12]), "+f"(d[13]), "+f"(d[14]), "+f"(d[15]), "+f"(d[16]), "+f"(d[17]), "+f"(d[18]), "+f"(d[19]), "+f"(d[20]), "+f"(d[21]), "+f"(d[22]), "+f"(d[23]), "+f"(d[24]), "+f"(d[25]), "+f"(d[26]), "+f"(d[27]), "+f"(d[28]), "+f"(d[29]), "+f"(d[30]), "+f"(d[31]), "+f"(d[32]), "+f"(d[33]), "+f"(d[34]), "+f"(d[35]), "+f"(d[36]), "+f"(d[37]), "+f"(d[38]), "+f"(d[39]), "+f"(d[40]), "+f"(d[41]), "+f"(d[42]), "+f"(d[43]), "+f"(d[44]), "+f"(d[45]), "+f"(d[46]), "+f"(d[47]), "+f"(d[48]), "+f"(d[49]), "+f"(d[50]), "+f"(d[51]), "+f"(d[52]), "+f"(d[53]), "+f"(d[54]), "+f"(d[55]), "+f"(d[56]), "+f"(d[57]), "+f"(d[58]), "+f"(d[59]), "+f"(d[60]), "+f"(d[61]), "+f"(d[62]), "+f"(d[63])
     : "l"(da), "l"(db), "n"(TB), "n"(TA));
  }
}
template<int TB, bool FIRST, int TA = 0> __device__ __forceinline__ void wgmma_n144(float (&d)[72], uint64_t da, uint64_t db){
  if (FIRST) {
    asm volatile("wgmma.mma_async.sync.aligned.m64n144k16.f32.bf16.bf16 {%0, %1, %2, %3, %4, %5, %6, %7, %8, %9, %10, %11, %12, %13, %14, %15, %16, %17, %18, %19, %20, %21, %22, %23, %24, %25, %26, %27, %28, %29, %30, %31, %32, %33, %34, %35, %36, %37, %38, %39, %40, %41, %42, %43, %44, %45, %46, %47, %48, %49, %50, %51, %52, %53, %54, %55, %56, %57, %58, %59, %60, %61, %62, %63, %64, %65, %66, %67, %68, %69, %70, %71}, %72, %73, 0, 1, 1, %75, %74;"
     : "=f"(d[0]), "=f"(d[1]), "=f"(d[2]), "=f"(d[3]), "=f"(d[4]), "=f"(d[5]), "=f"(d[6]), "=f"(d[7]), "=f"(d[8]), "=f"(d[9]), "=f"(d[10]), "=f"(d[11]), "=f"(d[12]), "=f"(d[13]), "=f"(d[14]), "=f"(d[15]), "=f"(d[16]), "=f"(d[17]), "=f"(d[18]), "=f"(d[19]), "=f"(d[20]), "=f"(d[21]), "=f"(d[22]), "=f"(d[23]), "=f"(d[24]), "=f"(d[25]), "=f"(d[26]), "=f"(d[27]), "=f"(d[28]), "=f"(d[29]), "=f"(d[30]), "=f"(d[31]), "=f"(d[32]), "=f"(d[33]), "=f"(d[34]), "=f"(d[35]), "=f"(d[36]), "=f"(d[37]), "=f"(d[38]), "=f"(d[39]), "=f"(d[40]), "=f"(d[41]), "=f"(d[42]), "=f"(d[43]), "=f"(d[44]), "=f"(d[45]), "=f"(d[46]), "=f"(d[47]), "=f"(d[48]), "=f"(d[49]), "=f"(d[50]), "=f"(d[51]), "=f"(d[52]), "=f"(d[53]), "=f"(d[54]), "=f"(d[55]), "=f"(d[56]), "=f"(d[57]), "=f"(d[58]), "=f"(d[59]), "=f"(d[60]), "=f"(d[61]), "=f"(d[62]), "=f"(d[63]), "=f"(d[64]), "=f"(d[65]), "=f"(d[66]), "=f"(d[67]), "=f"(d[68]), "=f"(d[69]), "=f"(d[70]), "=f"(d[71])
     : "l"(da), "l"(db), "n"(TB), "n"(TA));
  } else {
    asm volatile("wgmma.mma_async.sync.aligned.m64n144k16.f32.bf16.bf16 {%0, %1, %2, %3, %4, %5, %6, %7, %8, %9, %10, %11, %12, %13, %14, %15, %16, %17, %18, %19, %20, %21, %22, %23, %24, %25, %26, %27, %28, %29, %30, %31, %32, %33, %34, %35, %36, %37, %38, %39, %40, %41, %42, %43, %44, %45, %46, %47, %48, %49, %50, %51, %52, %53, %54, %55, %56, %57, %58, %59, %60, %61, %62, %63, %64, %65, %66, %67, %68, %69, %70, %71}, %72, %73, 1, 1, 1, %75, %74;"
     : "+f"(d[0]), "+f"(d[1]), "+f"(d[2]), "+f"(d[3]), "+f"(d[4]), "+f"(d[5]), "+f"(d[6]), "+f"(d[7]), "+f"(d[8]), "+f"(d[9]), "+f"(d[10]), "+f"(d[11]), "+f"(d[12]), "+f"(d[13]), "+f"(d[14]), "+f"(d[15]), "+f"(d[16]), "+f"(d[17]), "+f"(d[18]), "+f"(d[19]), "+f"(d[20]), "+f"(d[21]), "+f"(d[22]), "+f"(d[23]), "+f"(d[24]), "+f"(d[25]), "+f"(d[26]), "+f"(d[27]), "+f"(d[28]), "+f"(d[29]), "+f"(d[30]), "+f"(d[31]), "+f"(d[32]), "+f"(d[33]), "+f"(d[34]), "+f"(d[35]), "+f"(d[36]), "+f"(d[37]), "+f"(d[38]), "+f"(d[39]), "+f"(d[40]), "+f"(d[41]), "+f"(d[42]), "+f"(d[43]), "+f"(d[44]), "+f"(d[45]), "+f"(d[46]), "+f"(d[47]), "+f"(d[48]), "+f"(d[49]), "+f"(d[50]), "+f"(d[51]), "+f"(d[52]), "+f"(d[53]), "+f"(d[54]), "+f"(d[55]), "+f"(d[56]), "+f"(d[57]), "+f"(d[58]), "+f"(d[59]), "+f"(d[60]), "+f"(d[61]), "+f"(d[62]), "+f"(d[63]), "+f"(d[64]), "+f"(d[65]), "+f"(d[66]), "+f"(d[67]), "+f"(d[68]), "+f"(d[69]), "+f"(d[70]), "+f"(d[71])
     : "l"(da), "l"(db), "n"(TB), "n"(TA));
  }
}
template<int TB, bool FIRST, int TA = 0> __device__ __forceinline__ void wgmma_n192(float (&d)[96], uint64_t da, uint64_t db){
  if (FIRST) {
    asm volatile("wgmma.mma_async.sync.aligned.m64n192k16.f32.bf16.bf16 {%0, %1, %2, %3, %4, %5, %6, %7, %8, %9, %10, %11, %12, %13, %14, %15, %16, %17, %18, %19, %20, %21, %22, %23, %24, %25, %26, %27, %28, %29, %30, %31, %32, %33, %34, %35, %36, %37, %38, %39, %40, %41, %42, %43, %44, %45, %46, %47, %48, %49, %50, %51, %52, %53, %54, %55, %56, %57, %58, %59, %60, %61, %62, %63, %64, %65, %66, %67, %68, %69, %70, %71, %72, %73, %74, %75, %76, %77, %78, %79, %80, %81, %82, %83, %84, %85, %86, %87, %88, %89, %90, %91, %92, %93, %94, %95}, %96, %97, 0, 1, 1, %99, %98;"
     : "=f"(d[0]), "=f"(d[1]), "=f"(d[2]), "=f"(d[3]), "=f"(d[4]), "=f"(d[5]), "=f"(d[6]), "=f"(d[7]), "=f"(d[8]), "=f"(d[9]), "=f"(d[10]), "=f"(d[11]), "=f"(d[12]), "=f"(d[13]), "=f"(d[14]), "=f"(d[15]), "=f"(d[16]), "=f"(d[17]), "=f"(d[18]), "=f"(d[19]), "=f"(d[20]), "=f"(d[21]), "=f"(d[22]), "=f"(d[23]), "=f"(d[24]), "=f"(d[25]), "=f"(d[26]), "=f"(d[27]), "=f"(d[28]), "=f"(d[29]), "=f"(d[30]), "=f"(d[31]), "=f"(d[32]), "=f"(d[33]), "=f"(d[34]), "=f"(d[35]), "=f"(d[36]), "=f"(d[37]), "=f"(d[38]), "=f"(d[39]), "=f"(d[40]), "=f"(d[41]), "=f"(d[42]), "=f"(d[43]), "=f"(d[44]), "=f"(d[45]), "=f"(d[46]), "=f"(d[47]), "=f"(d[48]), "=f"(d[49]), "=f"(d[50]), "=f"(d[51]), "=f"(d[52]), "=f"(d[53]), "=f"(d[54]), "=f"(d[55]), "=f"(d[56]), "=f"(d[57]), "=f"(d[58]), "=f"(d[59]), "=f"(d[60]), "=f"(d[61]), "=f"(d[62]), "=f"(d[63]), "=f"(d[64]), "=f"(d[65]), "=f"(d[66]), "=f"(d[67]), "=f"(d[68]), "=f"(d[69]), "=f"(d[70]), "=f"(d[71]), "=f"(d[72]), "=f"(d[73]), "=f"(d[74]), "=f"(d[75]), "=f"(d[76]), "=f"(d[77]), "=f"(d[78]), "=f"(d[79]), "=f"(d[80]), "=f"(d[81]), "=f"(d[82]), "=f"(d[83]), "=f"(d[84]), "=f"(d[85]), "=f"(d[86]), "=f"(d[87]), "=f"(d[88]), "=f"(d[89]), "=f"(d[90]), "=f"(d[91]), "=f"(d[92]), "=f"(d[93]), "=f"(d[94]), "=f"(d[95])
     : "l"(da), "l"(db), "n"(TB), "n"(TA));
  } else {
    asm volatile("wgmma.mma_async.sync.aligned.m64n192k16.f32.bf16.bf16 {%0, %1, %2, %3, %4, %5, %6, %7, %8, %9, %10, %11, %12, %13, %14, %15, %16, %17, %18, %19, %20, %21, %22, %23, %24, %25, %26, %27, %28, %29, %30, %31, %32, %33, %34, %35, %36, %37, %38, %39, %40, %41, %42, %43, %44, %45, %46, %47, %48, %49, %50, %51, %52, %53, %54, %55, %56, %57, %58, %59, %60, %61, %62, %63, %64, %65, %66, %67, %68, %69, %70, %71, %72, %73, %74, %75, %76, %77, %78, %79, %80, %81, %82, %83, %84, %85, %86, %87, %88, %89, %90, %91, %92, %93, %94, %95}, %96, %97, 1, 1, 1, %99, %98;"
     : "+f"(d[0]), "+f"(d[1]), "+f"(d[2]), "+f"(d[3]), "+f"(d[4]), "+f"(d[5]), "+f"(d[6]), "+f"(d[7]), "+f"(d[8]), "+f"(d[9]), "+f"(d[10]), "+f"(d[11]), "+f"(d[12]), "+f"(d[13]), "+f"(d[14]), "+f"(d[15]), "+f"(d[16]), "+f"(d[17]), "+f"(d[18]), "+f"(d[19]), "+f"(d[20]), "+f"(d[21]), "+f"(d[22]), "+f"(d[23]), "+f"(d[24]), "+f"(d[25]), "+f"(d[26]), "+f"(d[27]), "+f"(d[28]), "+f"(d[29]), "+f"(d[30]), "+f"(d[31]), "+f"(d[32]), "+f"(d[33]), "+f"(d[34]), "+f"(d[35]), "+f"(d[36]), "+f"(d[37]), "+f"(d[38]), "+f"(d[39]), "+f"(d[40]), "+f"(d[41]), "+f"(d[42]), "+f"(d[43]), "+f"(d[44]), "+f"(d[45]), "+f"(d[46]), "+f"(d[47]), "+f"(d[48]), "+f"(d[49]), "+f"(d[50]), "+f"(d[51]), "+f"(d[52]), "+f"(d[53]), "+f"(d[54]), "+f"(d[55]), "+f"(d[56]), "+f"(d[57]), "+f"(d[58]), "+f"(d[59]), "+f"(d[60]), "+f"(d[61]), "+f"(d[62]), "+f"(d[63]), "+f"(d[64]), "+f"(d[65]), "+f"(d[66]), "+f"(d[67]), "+f"(d[68]), "+f"(d[69]), "+f"(d[70]), "+f"(d[71]), "+f"(d[72]), "+f"(d[73]), "+f"(d[74]), "+f"(d[75]), "+f"(d[76]), "+f"(d[77]), "+f"(d[78]), "+f"(d[79]), "+f"(d[80]), "+f"(d[81]), "+f"(d[82]), "+f"(d[83]), "+f"(d[84]), "+f"(d[85]), "+f"(d[86]), "+f"(d[87]), "+f"(d[88]), "+f"(d[89]), "+f"(d[90]), "+f"(d[91]), "+f"(d[92]), "+f"(d[93]), "+f"(d[94]), "+f"(d[95])
     : "l"(da), "l"(db), "n"(TB), "n"(TA));
  }
}

__device__ __forceinline__ uint32_t clock32() { uint32_t t; asm volatile("mov.u32 %0, %%clock;" : "=r"(t)); return t; }
__device__ __forceinline__ bool elect_one() {
  uint32_t pred;
  asm volatile("{\n.reg .pred p;\nelect.sync _|p, 0xffffffff;\nselp.u32 %0, 1, 0, p;\n}" : "=r"(pred));
  return pred != 0;
}
__device__ __forceinline__ void mbar_init(uint32_t b, int c) { asm volatile("mbarrier.init.shared::cta.b64 [%0], %1;" ::"r"(b), "r"(c) : "memory"); }
__device__ __forceinline__ void mbar_expect(uint32_t b, int bytes) { asm volatile("mbarrier.arrive.expect_tx.shared::cta.b64 _, [%0], %1;" ::"r"(b), "r"(bytes) : "memory"); }
__device__ __forceinline__ void mbar_arrive(uint32_t b) { asm volatile("mbarrier.arrive.shared::cta.b64 _, [%0];" ::"r"(b) : "memory"); }
__device__ __forceinline__ void mbar_arrive_if(uint32_t b, uint32_t pred) {
  asm volatile("{\n.reg .pred p;\nsetp.ne.u32 p, %1, 0;\n@p mbarrier.arrive.shared::cta.b64 _, [%0];\n}" ::"r"(b), "r"(pred) : "memory");
}
#define WAIT_LIMIT "2000000"
#define DIE_ADDR "l"(0ull)
#define DIE_ST "st.global.u32 [%2], %1;\n"
__device__ __forceinline__ void mbar_wait(uint32_t b, uint32_t ph) {
  asm volatile(
      "{\n.reg .pred p;\n.reg .u32 c;\nmov.u32 c, 0;\n"
      "W:\nmbarrier.try_wait.parity.shared::cta.b64 p, [%0], %1, 1000;\n@p bra D;\n"
      "add.u32 c, c, 1;\nsetp.lt.u32 p, c, " WAIT_LIMIT ";\n@p bra W;\n" DIE_ST
      "D:\n}" ::"r"(b), "r"(ph), DIE_ADDR : "memory");
}
__device__ __forceinline__ uint32_t mbar_test(uint32_t b, uint32_t ph) {
  uint32_t ok;
  asm volatile("{\n.reg .pred p;\nmbarrier.test_wait.parity.shared::cta.b64 p, [%1], %2;\nselp.u32 %0, 1, 0, p;\n}" : "=r"(ok) : "r"(b), "r"(ph) : "memory");
  return ok;
}
__device__ __forceinline__ void cnt_arrive(int idx) {
  asm volatile("red.release.gpu.global.add.u32 [%0], 1;" ::"l"(&g_cnt[idx * CNT_STRIDE]) : "memory");
}
__device__ __forceinline__ void cnt_wait(uint32_t idx, uint32_t target) {
  asm volatile(
      "{\n.reg .pred p;\n.reg .u32 c, v;\nmov.u32 c, 0;\n"
      "W:\nld.acquire.gpu.global.u32 v, [%3];\nsub.u32 v, v, %1;\nsetp.ge.s32 p, v, 0;\n@p bra D;\n"
      "add.u32 c, c, 1;\nsetp.lt.u32 p, c, " WAIT_LIMIT ";\n@p bra W;\n" DIE_ST
      "D:\n}" ::"r"(idx | 0x80000000u), "r"(target), DIE_ADDR, "l"(&g_cnt[idx * CNT_STRIDE]) : "memory");
}
__device__ __forceinline__ void release_x(uint32_t fdone, uint32_t ph, int cnt, int n, uint32_t mask, int ev) {
#pragma unroll 1
  for (int k = 0; k < n;) {
    int e = k + __ffs(mask >> k);
    mbar_wait(fdone + 8 * (e - 1), ph);
    if (ev) for (int j = k; j < e; j++) EV(32 + j);
    asm volatile("fence.release.gpu;" ::: "memory");
    asm volatile("red.relaxed.gpu.global.add.u32 [%0], 1;" ::"l"(&g_cnt[(cnt + e - 1) * CNT_STRIDE]) : "memory");
    if (ev) for (int j = k; j < e; j++) EV(48 + j);
    k = e;
  }
}
__device__ __forceinline__ uint4 lds128(uint32_t a) {
  uint4 v;
  asm volatile("ld.shared.v4.u32 {%0,%1,%2,%3}, [%4];" : "=r"(v.x), "=r"(v.y), "=r"(v.z), "=r"(v.w) : "r"(a) : "memory");
  return v;
}
__device__ __forceinline__ void stat_publish(ulonglong2* p, float s, float qq, uint32_t ep1) {
  const float mean = s * (1.0f / DM);
  const float rstd = rsqrtf(fmaxf(qq * (1.0f / DM) - mean * mean, 0.f) + 1e-5f);
  const unsigned long long tag = (unsigned long long)ep1 << 32;
  asm volatile("st.relaxed.gpu.global.v2.u64 [%0], {%1, %2};" ::"l"(p), "l"(tag | __float_as_uint(rstd)), "l"(tag | __float_as_uint(-mean)) : "memory");
}
__device__ __forceinline__ void stat_gather(const ulonglong2* p, uint32_t tag, float* rsd, float* md) {
  unsigned long long a[4], b[4];
#pragma unroll 1
  for (uint32_t it = 0;; it++) {
    bool ok = true;
#pragma unroll
    for (int i = 0; i < 4; i++) asm volatile("ld.relaxed.gpu.global.v2.u64 {%0, %1}, [%2];" : "=l"(a[i]), "=l"(b[i]) : "l"(p + i * 32) : "memory");
#pragma unroll
    for (int i = 0; i < 4; i++) ok = ok && (uint32_t)(a[i] >> 32) == tag && (uint32_t)(b[i] >> 32) == tag;
    if (ok) break;
    if (it > 2000000u) { asm volatile("st.global.u32 [%0], %1;" ::"l"(0ull), "r"(0) : "memory"); break; }
  }
#pragma unroll
  for (int i = 0; i < 4; i++) {
    rsd[i * 32] = __uint_as_float((uint32_t)a[i]);
    if (md) md[i * 32] = __uint_as_float((uint32_t)b[i]);
  }
}
__device__ __forceinline__ void pace(uint32_t t0, uint32_t dt) { while (clock32() - t0 < dt) __nanosleep(20); }
__device__ __forceinline__ void spin_until(uint32_t t) {
  asm volatile("{\n.reg .pred p;\n.reg .u32 c;\nW:\nmov.u32 c, %%clock;\nsub.u32 c, c, %0;\nsetp.lt.s32 p, c, 0;\n@p nanosleep.u32 40;\n@p bra W;\n}" ::"r"(t) : "memory");
}
__device__ __forceinline__ void tma2d(uint32_t dst, const CUtensorMap* m, uint32_t bar, int c0, int c1) {
  asm volatile("cp.async.bulk.tensor.2d.shared::cluster.global.mbarrier::complete_tx::bytes [%0], [%1, {%3, %4}], [%2];" ::"r"(dst), "l"(m), "r"(bar), "r"(c0), "r"(c1) : "memory");
}
__device__ __forceinline__ void tma2d_ef(uint32_t dst, const CUtensorMap* m, uint32_t bar, int c0, int c1) {
  asm volatile("{\n.reg .b64 pol;\ncreatepolicy.fractional.L2::evict_first.b64 pol, 1.0;\n"
               "cp.async.bulk.tensor.2d.shared::cluster.global.mbarrier::complete_tx::bytes.L2::cache_hint [%0], [%1, {%3, %4}], [%2], pol;\n}"
               ::"r"(dst), "l"(m), "r"(bar), "r"(c0), "r"(c1) : "memory");
}
__device__ __forceinline__ void tma3d(uint32_t dst, const CUtensorMap* m, uint32_t bar, int c0, int c1, int c2) {
  asm volatile("cp.async.bulk.tensor.3d.shared::cluster.global.mbarrier::complete_tx::bytes [%0], [%1, {%3, %4, %5}], [%2];" ::"r"(dst), "l"(m), "r"(bar), "r"(c0), "r"(c1), "r"(c2) : "memory");
}
__device__ __forceinline__ void bulk_pf(const void* p, int bytes) {
  asm volatile("cp.async.bulk.prefetch.L2.global [%0], %1;" ::"l"(p), "r"(bytes) : "memory");
}
__device__ __forceinline__ void tma_st2d(const CUtensorMap* m, uint32_t src, int c0, int c1) {
  asm volatile("cp.async.bulk.tensor.2d.global.shared::cta.tile.bulk_group [%0, {%2, %3}], [%1];" ::"l"(m), "r"(src), "r"(c0), "r"(c1) : "memory");
}
__device__ __forceinline__ void tma_red2d(const CUtensorMap* m, uint32_t src, int c0, int c1) {
  asm volatile("cp.reduce.async.bulk.tensor.2d.global.shared::cta.add.tile.bulk_group [%0, {%2, %3}], [%1];" ::"l"(m), "r"(src), "r"(c0), "r"(c1) : "memory");
}
__device__ __forceinline__ void bulk_commit() { asm volatile("cp.async.bulk.commit_group;" ::: "memory"); }
__device__ __forceinline__ void bulk_wait0() { asm volatile("cp.async.bulk.wait_group 0;" ::: "memory"); }
__device__ __forceinline__ void fence_async_smem() { asm volatile("fence.proxy.async.shared::cta;" ::: "memory"); }
__device__ __forceinline__ void fence_async_all() { asm volatile("fence.proxy.async.global;" ::: "memory"); }
__device__ __forceinline__ void wg_fence() { asm volatile("wgmma.fence.sync.aligned;" ::: "memory"); }
__device__ __forceinline__ void wg_commit() { asm volatile("wgmma.commit_group.sync.aligned;" ::: "memory"); }
template <int N> __device__ __forceinline__ void wg_wait() { asm volatile("wgmma.wait_group.sync.aligned %0;" ::"n"(N) : "memory"); }
__device__ __forceinline__ uint32_t pk(float a, float b) {
  uint32_t r;
  asm("cvt.rn.bf16x2.f32 %0, %1, %2;" : "=r"(r) : "f"(b), "f"(a));
  return r;
}
__device__ __forceinline__ uint32_t pk_relu(float a, float b) {
  uint32_t r;
  asm("cvt.rn.relu.bf16x2.f32 %0, %1, %2;" : "=r"(r) : "f"(b), "f"(a));
  return r;
}
__device__ __forceinline__ float bf_lo(uint32_t v) { return __uint_as_float(v << 16); }
__device__ __forceinline__ float bf_hi(uint32_t v) { return __uint_as_float(v & 0xffff0000u); }
__device__ __forceinline__ void stsm4(uint32_t addr, uint32_t a0, uint32_t a1, uint32_t a2, uint32_t a3) {
  asm volatile("stmatrix.sync.aligned.m8n8.x4.shared.b16 [%0], {%1,%2,%3,%4};" ::"r"(addr), "r"(a0), "r"(a1), "r"(a2), "r"(a3));
}
__device__ __forceinline__ float lds32f(uint32_t a) {
  float v;
  asm volatile("ld.shared.f32 %0, [%1];" : "=f"(v) : "r"(a) : "memory");
  return v;
}
__device__ __forceinline__ float2 lds64f(uint32_t a) {
  float2 v;
  asm volatile("ld.shared.v2.f32 {%0,%1}, [%2];" : "=f"(v.x), "=f"(v.y) : "r"(a) : "memory");
  return v;
}
template <int R> __device__ __forceinline__ void reg_fence(float (&d)[R]) {
#pragma unroll
  for (int i = 0; i < R; i++) asm volatile("" : "+f"(d[i])::"memory");
}
constexpr uint32_t DESC_HI_128 = (1024u >> 4) | (1u << 30);
__device__ __forceinline__ uint64_t desc(uint32_t lo, uint32_t hi) {
  uint64_t d;
  asm("mov.b64 %0, {%1, %2};" : "=l"(d) : "r"(lo), "r"(hi));
  return d;
}

__device__ __forceinline__ void sum8(uint4 v, float& s, float& q) {
  float a;
  a = bf_lo(v.x); s += a; q = fmaf(a, a, q);  a = bf_hi(v.x); s += a; q = fmaf(a, a, q);
  a = bf_lo(v.y); s += a; q = fmaf(a, a, q);  a = bf_hi(v.y); s += a; q = fmaf(a, a, q);
  a = bf_lo(v.z); s += a; q = fmaf(a, a, q);  a = bf_hi(v.z); s += a; q = fmaf(a, a, q);
  a = bf_lo(v.w); s += a; q = fmaf(a, a, q);  a = bf_hi(v.w); s += a; q = fmaf(a, a, q);
}

__device__ __forceinline__ int dslot(int layer, int s) { return ((layer ? 0xC9 : 0xE4) >> ((s & 3) * 2)) & 3; }

#define G3A_C1 8
#define G3B_C1 6
#define G3A_C2 12
#define G3B_C2 10
#define MAPMODE 1
#define CLUSTER 2
#define CPF_DT 520
#define CPF_LAG 3
#define CPF_START -1
#define CLD_DT 900
#define FLUSH_DT 750
#define FLUSH_DT_LAST 0
#define STAGGER 1
#define FRONT 0
#define EVPH 2
#define FLUSH_DT_D 300
#define CPF2_DT 500
#define HPF_D_START 78000
#define HW1_START 10000
#define HPF_C_START 50000
#define XEARLY2 3
#define XEARLY4 6
#define FLUSH_DT4 200
#define RELMASK2 0x1AC
#define RELMASK4 0x12A
#define FLUSH_DT_C 750
#define XFIRST 5
#define AG_DT 200
#define GO_EARLY 1
#define CL0_T0 1000
#define REST_AFTER 0
#define REST_T0 600
#define CE1 6
#define CE1_DT 1600
#define CL0_DT 1250
#define CL0_DT2 1000
#define CL0_N 6
#define CEARLY 2
#define XLD_DT 600
#define XLD_T0 0

__global__ void __launch_bounds__(384, 1)
fnet_ffn_kernel(const __grid_constant__ Maps maps, const __nv_bfloat16* __restrict__ xin, const __nv_bfloat16* __restrict__ cre,
                const __nv_bfloat16* __restrict__ cim, const __nv_bfloat16* __restrict__ dre,
                const __nv_bfloat16* __restrict__ dim, const __nv_bfloat16* __restrict__ w1, const __nv_bfloat16* __restrict__ w2,
                __nv_bfloat16* xout) {
  extern __shared__ __align__(1024) unsigned char smem[];
  const uint32_t sb = __shfl_sync(0xffffffffu, (uint32_t)__cvta_generic_to_shared(smem), 0);
  constexpr uint32_t sbd = 1024;
  const int tid = threadIdx.x;
  const int wg = __shfl_sync(0xffffffffu, tid >> 7, 0);
  const int warp = __shfl_sync(0xffffffffu, (tid >> 5) & 3, 0);
  const int lane = tid & 31;
  if (tid == 0) EV(110);
  if (blockIdx.x < NHELP) {
    if (tid == 0) atomicAdd(&g_cnt[CNT_TICKET * CNT_STRIDE], 1u);
    const uint32_t th0 = clock32();
    constexpr int HS = 16, HG = DFF / 192 / NHELP;
    const uint32_t hb = sb + HS * B_SLOT + 8192;
    if (tid == 0) {
#pragma unroll
      for (int i = 0; i < 2 * HS; i++) mbar_init(hb + 8 * i, 1);
      asm volatile("fence.mbarrier_init.release.cluster;" ::: "memory");
    }
    for (int i = tid; i < 2048; i += 384) reinterpret_cast<uint32_t*>(smem + HS * B_SLOT)[i] = 0x3f803f80u;
    fence_async_smem();
    __syncthreads();
    if (wg == 0) {
      int slot = 0, ph = 0;
#pragma unroll 1
      for (int g = 0; g < HG; g++) {
        float acc[96];
#pragma unroll
        for (int i = 0; i < 96; i++) acc[i] = 0.f;
#pragma unroll 1
        for (int st = 0; st < 18; st++) {
          mbar_wait(hb + 8 * slot, ph);
          const uint32_t blo = (((sbd + slot * B_SLOT) >> 4) | ((4096u >> 4) << 16));
          const uint64_t da = desc(((sbd + HS * B_SLOT) >> 4) | (1u << 16), DESC_HI_128);
          wg_fence();
          wgmma_n192<1, false>(acc, da, desc(blo, DESC_HI_128));
          wgmma_n192<1, false>(acc, da, desc(blo + 128, DESC_HI_128));
          wg_commit();
          wg_wait<1>();
          mbar_arrive_if(hb + 8 * (HS + ((slot + HS - 1) & (HS - 1))), tid == 0 && (g | st));
          if (++slot == HS) { slot = 0; ph ^= 1; }
        }
        wg_wait<0>();
        reg_fence(acc);
        if (tid < 4) {
#pragma unroll
          for (int b = 0; b < 24; b++)
            *reinterpret_cast<float2*>(g_cs1 + (blockIdx.x * HG + g) * 192 + b * 8 + tid * 2) = make_float2(acc[b * 4], acc[b * 4 + 1]);
        }
      }
      __syncwarp();
      if (tid == 0) { cnt_arrive(CNT_CS); EV(100); }
    } else if (tid == 128) {
      int slot = 0, ph = 1;
      pace(th0, HW1_START);
#pragma unroll 1
      for (int i = 0; i < HG * 18; i++) {
        mbar_wait(hb + 8 * (HS + slot), ph);
        mbar_expect(hb + 8 * slot, B_SLOT);
        tma3d(sb + slot * B_SLOT, &maps.w1, hb + 8 * slot, 0, (i % 18) * 32, (blockIdx.x * HG + i / 18) * 3);
        if (++slot == HS) { slot = 0; ph ^= 1; }
      }
      constexpr int W2N = DM * DFF * 2 / NHELP / 8192;
#pragma unroll 1
      for (int i = 0; i < W2N; i++) bulk_pf(reinterpret_cast<const char*>(w2) + (size_t)(blockIdx.x * W2N + i) * 8192, 8192);
      EV(101);
      pace(th0, HPF_D_START);
#pragma unroll 1
      for (int i = 0; i < 81; i++) bulk_pf(reinterpret_cast<const char*>((blockIdx.x & 1) ? dim : dre) + ((blockIdx.x >> 1) * 81 + i) * 4096, 4096);
      EV(102);
    }
    return;
  }
  const int cta = blockIdx.x - NHELP;
  const int r = (cta & 1) | ((cta >> 4) << 1), p = (cta >> 1) & 7;
  const int m = p >> 2, q = p & 3;
  const uint32_t bar0 = sb + OFF_BAR;
#define BAR(i) (bar0 + 8u * (uint32_t)(i))
#define START_SYNC() do { __syncwarp(); asm volatile("bar.sync 0, 384;" ::: "memory"); } while (0)

  uint32_t ticket = 0;
  if (elect_one()) {
    const int w12 = wg * 4 + warp;
#pragma unroll
    for (int i = 0; i < 16; i++) mbar_init(BAR(w12 * 16 + i), w12 < 2 ? 4 : 1);
    asm volatile("fence.mbarrier_init.release.cluster;" ::: "memory");
    if (w12 == 8) {
      fence_async_smem();
#pragma unroll 1
      for (int k = 0; k < XFIRST; k++) {
        mbar_expect(BAR(BAR_XF + k), A_SLOT);
        tma2d(sb + OFF_A + k * A_SLOT, &maps.xin, BAR(BAR_XF + k), k * 64, r * 128);
        if (k < 4) {
          mbar_expect(BAR(BAR_DF + k), D_SLOT);
          tma3d(sb + OFF_B + k * D_SLOT, m ? &maps.di : &maps.dr, BAR(BAR_DF + k), k * 64, q * 48, 0);
        }
      }
    }
  }
  __syncwarp();
  if (tid == 320) asm volatile("atom.relaxed.gpu.global.add.u32 %0, [%1], 1;" : "=r"(ticket) : "l"(&g_cnt[CNT_TICKET * CNT_STRIDE]));

  if (wg == 2) {
    asm volatile("setmaxnreg.dec.sync.aligned.u32 40;");
    if (warp & 1) START_SYNC();
    if (warp == 0) {
      const CUtensorMap* mD = m ? &maps.di : &maps.dr;
      START_SYNC();
      if (elect_one()) {
        EV(113);
        int slot = 0, ph = 1;
#pragma unroll 1
        for (int layer = 0; layer < 2; layer++) {
#pragma unroll 1
          for (int s = 0; s < 9; s++) {
            if (s < 3) {
              const int nacq = (s == 0 || s + layer == 2) ? 2 : 1;
#pragma unroll 1
              for (int i = 0; i < nacq; i++) {
                mbar_wait(BAR(BAR_BEMPTY + slot), ph);
                mbar_arrive(BAR(BAR_BFULL + slot));
                if (++slot == NB) { slot = 0; ph ^= 1; }
              }
            } else if (s == 3) {
              if (layer) mbar_wait(BAR(BAR_FDONE + 16), 0);
            } else {
              mbar_wait(BAR(BAR_RG1 + s - 4), layer);
            }
            if (layer || s >= 4) {
              mbar_expect(BAR(BAR_DF + s), D_SLOT);
              tma3d(sb + OFF_B + dslot(layer, s) * D_SLOT, mD, BAR(BAR_DF + s), s * 64, q * 48, 0);
              const int k = s - 4 + XFIRST;
              if (layer == 0 && k < 9) {
                mbar_expect(BAR(BAR_XF + k), A_SLOT);
                tma2d(sb + OFF_A + k * A_SLOT, &maps.xin, BAR(BAR_XF + k), k * 64, r * 128);
              }
            }
          }
#pragma unroll 1
          for (int sg = -2; sg < 18; sg++) {
            const CUtensorMap* mm;
            int row, atom, cw, n, dk = 32;
            if (sg < 4) {
              mm = &maps.abld; row = (layer * 2 + m) * SEQ + q * 512;
              if (sg < 2) { mbar_wait(BAR(BAR_ABOK + sg + 2), layer); row += (sg + 2) * 128; atom = 0; cw = 1; n = 4; if (sg == -2) EV(6 + layer * 16); }
              else { mbar_wait(BAR(BAR_FOK), layer); atom = (sg - 1) * 3; cw = sg & 1; n = 16; }
            } else if (sg < 13) {
              mm = &maps.w1;
              if (sg < 10) {
                cw = sg & 1;
                const int c1 = cw ? G3B_C1 : G3A_C1, c2 = cw ? G3B_C2 : G3A_C2;
                const int lo = sg < 6 ? 0 : (sg < 8 ? c1 : c2), hi = sg < 6 ? c1 : (sg < 8 ? c2 : 18);
                atom = p * 9 + cw * 3; row = lo * 32; n = hi - lo;
              } else { cw = 0; atom = p * 9 + 6; row = (12 - sg) * 192; n = 6; }
            } else {
              row = p * 576; cw = sg & 1;
              atom = (sg - 13) * 2;
              if (sg < 17) { mm = &maps.w2; n = 12; dk = 48; }
              else { mm = &maps.w2n; n = 6; dk = 96; }
            }
            const uint32_t fb0 = BAR(BAR_BFULL);
#pragma unroll 1
            for (int i = 0; i < n; i++) {
              mbar_wait(BAR(BAR_BEMPTY + slot), ph);
              mbar_expect(fb0 + 8 * slot, B_SLOT);
              tma3d(sb + OFF_B + slot * B_SLOT, mm, fb0 + 8 * slot, 0, row, atom);
              row += dk;
              if (++slot == NB) { slot = 0; ph ^= 1; }
            }
          }
        }
      }
    } else if (warp == 1) {
      if (lane == 0) {
        asm volatile("prefetch.tensormap [%0];" ::"l"(m ? &maps.ci : &maps.cr) : "memory");
        asm volatile("prefetch.tensormap [%0];" ::"l"(&maps.abst) : "memory");
        asm volatile("prefetch.tensormap [%0];" ::"l"(&maps.abld) : "memory");
      }
      mbar_wait(BAR(BAR_EPOCH), 0);
      const uint32_t ep1 = *reinterpret_cast<volatile uint32_t*>(smem + OFF_EPOCH);
      {
        unsigned long long a[3], b[3];
#pragma unroll 1
        for (uint32_t it = 0;; it++) {
          bool ok = true;
#pragma unroll
          for (int i = 0; i < 3; i++)
            asm volatile("ld.relaxed.gpu.global.v2.u64 {%0, %1}, [%2];" : "=l"(a[i]), "=l"(b[i]) : "l"(&g_csd[p * 144 + min(lane + i * 32, 71) * 2]) : "memory");
#pragma unroll
          for (int i = 0; i < 3; i++) ok = ok && (uint32_t)(a[i] >> 32) == ep1 && (uint32_t)(b[i] >> 32) == ep1;
          if (ok) break;
          if (it > 2000000u) { asm volatile("st.global.u32 [%0], %1;" ::"l"(0ull), "r"(0) : "memory"); break; }
        }
#pragma unroll
        for (int i = 0; i < 3; i++)
          reinterpret_cast<float2*>(smem + OFF_CSD)[min(lane + i * 32, 71)] = make_float2(__uint_as_float((uint32_t)a[i]), __uint_as_float((uint32_t)b[i]));
        __syncwarp();
        mbar_arrive_if(BAR(BAR_CSD), lane == 0);
        if (lane == 0) EV(10);
      }
      if (lane == 0) {
#pragma unroll 1
        for (int layer = 0; layer < 2; layer++) {
          const int abrow = (layer * 2 + m) * SEQ + r * 128;
          const int abcnt = CNT_AB + ((layer * 2 + m) * 16 + r) * 2;
          mbar_wait(BAR(BAR_ABSTG), layer);
          EV(3 + layer * 16);
          tma_st2d(&maps.abst, sb + OFF_STG, q * 48, abrow);
          bulk_commit();
          bulk_wait0();
          EV(4 + layer * 16);
          cnt_arrive(abcnt);
          EV(5 + layer * 16);
          mbar_wait(BAR(BAR_ABSTG + 1), layer);
          mbar_wait(BAR(BAR_ABOK + REST_AFTER), layer);
          spin_until(clock32() + REST_T0);
          tma_st2d(&maps.abst, sb + OFF_A + 7 * A_SLOT, 192 + q * 48, abrow);
          bulk_commit();
          bulk_wait0();
          mbar_arrive(BAR(BAR_A7));
          tma_st2d(&maps.abst, sb + OFF_A + 8 * A_SLOT, 384 + q * 48, abrow);
          bulk_commit();
          bulk_wait0();
          cnt_arrive(abcnt + 1);
          release_x(BAR(BAR_FDONE), layer, CNT_X + (layer * 2 * 16 + r) * 9, 6, RELMASK2, EVPH == layer * 2);
          {
            uint32_t tn = 0;
#pragma unroll 1
            for (int i = 0; i < 8; i++) {
              if ((i & 3) == 0) mbar_wait(BAR(BAR_FDONE + 7 + (i >> 2)), layer);
              if (i == 0) tn = clock32();
              spin_until(tn);
              tma_red2d(&maps.xred, sb + OFF_A + 7 * A_SLOT + i * 4096, 448 + (i >> 2) * 64, r * 128 + (i & 3) * 32);
              tma_red2d(&maps.xred, sb + OFF_A + 7 * A_SLOT + i * 4096 + 2048, 448 + (i >> 2) * 64, r * 128 + (i & 3) * 32 + 16);
              tn += AG_DT;
              if (i == 3) {
                bulk_commit();
                mbar_wait(BAR(BAR_FDONE + 6), layer);
                bulk_wait0();
                mbar_arrive(BAR(BAR_SENT));
              }
            }
            bulk_commit();
            bulk_wait0();
            if (EVPH == layer * 2) EV(40);
            cnt_arrive(CNT_X + (layer * 2 * 16 + r) * 9 + 8);
            if (EVPH == layer * 2) EV(56);
          }
#pragma unroll 1
          for (int s = 0; s < 3; s++) {
            mbar_wait(BAR(BAR_RG3C + s), layer);
            mbar_wait(BAR(BAR_RG3B + 6 + s), layer);
            mbar_expect(BAR(BAR_X1F + 9 + s), A_SLOT);
            tma2d(sb + OFF_A + (6 + s) * A_SLOT, &maps.xld, BAR(BAR_X1F + 9 + s), s * 64, r * 128);
          }
#pragma unroll 1
          for (int s = 0; s < 3; s++) mbar_wait(BAR(BAR_X1F + 9 + s), layer);
          cnt_arrive(CNT_G3 + layer * 16 + r);
          cnt_wait(CNT_G3 + layer * 16 + r, ep1 * 8);
          mbar_arrive(BAR(BAR_FOK + 1));
          if (layer == 0) release_x(BAR(BAR_FDONE + 9), 0, CNT_X + (16 + r) * 9, 6, RELMASK4, EVPH == 1);
          mbar_wait(BAR(BAR_FDONE + 17), layer);
          tma_red2d(&maps.xld, sb + OFF_A + 8 * A_SLOT, 512, r * 128);
          bulk_commit();
          bulk_wait0();
          if (layer == 0) {
            mbar_wait(BAR(BAR_FDONE + 16), 0);
            if (EVPH == 1) EV(40);
            asm volatile("fence.release.gpu;" ::: "memory");
            asm volatile("red.relaxed.gpu.global.add.u32 [%0], 1;" ::"l"(&g_cnt[(CNT_X + (16 + r) * 9 + 8) * CNT_STRIDE]) : "memory");
            if (EVPH == 1) EV(56);
          }
        }
      }
    } else if (warp == 2) {
      START_SYNC();
      if ((sb & 0x3FFFFu) != sbd) asm volatile("st.global.u32 [%0], %1;" ::"l"(0ull), "r"(0) : "memory");
      const uint32_t ep1 = __shfl_sync(0xffffffffu, ticket, 0) / NGRID + 1;
      if (lane == 0) {
        *reinterpret_cast<volatile uint32_t*>(smem + OFF_EPOCH) = ep1;
        mbar_arrive(BAR(BAR_EPOCH));
      }
      {
        stat_gather(&g_stat[r * 128 + lane], ep1, reinterpret_cast<float*>(smem + OFF_RS) + lane, reinterpret_cast<float*>(smem + OFF_MEAN) + lane);
        __syncwarp();
        mbar_arrive_if(BAR(BAR_STAT), lane == 0);
        if (lane == 0) EV(11);
      }
#pragma unroll 1
      for (int ph4 = 0; ph4 < 4; ph4++) {
        const int layer = ph4 >> 1, second = ph4 & 1;
        if (ph4) {
          const int pl = (ph4 - 1) >> 1, k = min(lane, 8);
          const uint32_t fd = BAR(BAR_FDONE + (second ? 0 : 9));
          const uint32_t fr = BAR(second ? (k < 8 ? BAR_RG2 + k : BAR_RG1 + 8) : BAR_RG4 + k);
          const uint32_t fb = BAR((second ? BAR_X1F : BAR_XF) + k);
          const int kr = k - 1 + __ffs((second ? RELMASK2 : RELMASK4) >> k);
          const uint32_t* flag = &g_cnt[(CNT_X + ((ph4 - 1) * 16 + r) * 9 + kr) * CNT_STRIDE];
          uint32_t state = lane >= 9 ? 2 : 0;
          bool needm = second;
          if (second) mbar_wait(BAR(BAR_STAT), layer);
          mbar_wait(fd, pl);
#pragma unroll 1
          for (uint32_t it = 0;; it++) {
            bool polled = false;
            if (state == 0 && mbar_test(fd + 8 * kr, pl)) {
              uint32_t c;
              asm volatile("ld.acquire.gpu.global.u32 %0, [%1];" : "=r"(c) : "l"(flag) : "memory");
              polled = true;
              if ((int32_t)(c - ep1 * 8) >= 0) {
                fence_async_all();
                state = 1;
                if (!second && k < XEARLY4) { mbar_arrive(BAR(BAR_XOK + k)); state = 2; }
                if (ph4 - 1 == EVPH) EV(64 + lane);
              }
            }
            if (state == 1 && mbar_test(fr, pl)) {
              mbar_expect(fb, A_SLOT);
              tma2d(sb + OFF_A + k * A_SLOT, &maps.xld, fb, k * 64, r * 128);
              state = 2;
              if (ph4 - 1 == EVPH) EV(80 + lane);
            }
            if (needm && (__ballot_sync(0xffffffffu, state != 0) & 0xff) == 0xff) {
              __syncwarp();
              float4 t;
              asm volatile("ld.relaxed.gpu.global.v4.f32 {%0,%1,%2,%3}, [%4];" : "=f"(t.x), "=f"(t.y), "=f"(t.z), "=f"(t.w) : "l"(&g_rsum[layer * SEQ + r * 128 + lane * 4]) : "memory");
              float4* mp = reinterpret_cast<float4*>(smem + OFF_MEAN) + lane;
              const float4 o = *mp;
              constexpr float inv = -1.0f / DM;
              *mp = make_float4(fmaf(t.x, inv, o.x), fmaf(t.y, inv, o.y), fmaf(t.z, inv, o.z), fmaf(t.w, inv, o.w));
              __syncwarp();
              mbar_arrive_if(BAR(BAR_STAT + 1), lane == 0);
              needm = false;
            }
            if (__all_sync(0xffffffffu, state == 2)) break;
            if (!__any_sync(0xffffffffu, polled)) __nanosleep(100);
            if (it > 4000000u) { asm volatile("st.global.u32 [%0], %1;" ::"l"(0ull), "r"(0) : "memory"); break; }
          }
        }
        if (!second) {
          int idx = CNT_AB + ((layer * 2 + m) * 16 + q * 4 + (lane & 3)) * 2 + (lane >> 2);
          uint32_t target = ep1 * 4;
          if (lane == 8 || lane == 9) idx = CNT_AB + ((layer * 2 + lane - 8) * 16 + r) * 2;
          if (lane == 10) { idx = CNT_XINIT + r; target = ep1 * 32; }
          uint32_t pend = lane < 11;
          mbar_wait(BAR(BAR_RG1 + 6), layer);
#pragma unroll 1
          for (uint32_t it = 0; __any_sync(0xffffffffu, pend); it++) {
            if (pend) {
              uint32_t v;
              asm volatile("ld.acquire.gpu.global.u32 %0, [%1];" : "=r"(v) : "l"(&g_cnt[idx * CNT_STRIDE]) : "memory");
              if ((int32_t)(v - target) >= 0) {
                fence_async_all();
                if (lane < 4) mbar_arrive(BAR(BAR_ABOK + lane));
                if (layer == 0 && lane < 8) EV(120 + lane);
                pend = 0;
              }
            }
            if (it > 2000000u) { asm volatile("st.global.u32 [%0], %1;" ::"l"(0ull), "r"(0) : "memory"); break; }
          }
          __syncwarp();
          mbar_arrive_if(BAR(BAR_FOK), lane == 0);
        }
      }
    } else {
      const CUtensorMap* mC = m ? &maps.ci : &maps.cr;
      const char* cbase = reinterpret_cast<const char*>((m ? cim : cre) + (size_t)(r * 128 + (lane >> 1)) * SEQ + q * 512) + (lane & 1) * 128;
      asm volatile("prefetch.global.L2 [%0];" ::"l"(cbase));
      const int myrow = r * 128 + p * 16 + (lane >> 1);
      if (lane < 16) {
#pragma unroll
        for (int i = 1; i < 3; i++) g_stat[i * SEQ + r * 128 + p * 16 + lane] = make_ulonglong2(0ull, 0ull);
      }
      auto cload = [&](int k) {
        if (elect_one()) {
          mbar_expect(BAR(BAR_CF + k), A_SLOT);
          tma2d_ef(sb + OFF_A + k * A_SLOT, mC, BAR(BAR_CF + k), q * 512 + k * 64, r * 128);
        }
        __syncwarp();
      };
      if (CPF_START >= 0) mbar_wait(BAR(BAR_XF + CPF_START), 0);
      uint32_t t0 = clock32();
      t0 += CL0_T0 + (cta & 3) * (CL0_DT / 4);
#pragma unroll 1
      for (int kc = 0; kc < 8; kc++) {
        if (kc == CL0_N) { mbar_wait(BAR(BAR_ABOK), 0); t0 = clock32() + (cta & 3) * (CL0_DT2 / 4); }
        spin_until(t0);
        t0 += kc < CL0_N ? CL0_DT : CL0_DT2;
        mbar_wait(BAR(kc < 7 ? BAR_RG1 + kc : BAR_A7), 0);
        cload(kc);
      }
      mbar_wait(BAR(BAR_EPOCH), 0);
      const uint32_t ep1 = *reinterpret_cast<volatile uint32_t*>(smem + OFF_EPOCH);
#pragma unroll 1
      for (int layer = 0; layer < 2; layer++) {
        if (layer) {
          if (elect_one()) {
#pragma unroll 1
            for (int kt = 0; kt < XEARLY4; kt++) {
              mbar_wait(BAR(BAR_XOK + kt), 0);
              mbar_wait(BAR(BAR_RG4 + kt), 0);
              if (kt == 0) t0 = clock32() + XLD_T0;
              spin_until(t0 + kt * XLD_DT);
              mbar_expect(BAR(BAR_XF + kt), A_SLOT);
              tma2d(sb + OFF_A + kt * A_SLOT, &maps.xld, BAR(BAR_XF + kt), kt * 64, r * 128);
              if (EVPH == 1) EV(80 + kt);
            }
          }
          __syncwarp();
          mbar_wait(BAR(BAR_S6), 0);
          t0 = clock32() + (cta & 3) * (CE1_DT / 4);
#pragma unroll 1
          for (int kc = 0; kc < 8; kc++) {
            if (kc == CE1) { mbar_wait(BAR(BAR_STAT), 1); mbar_wait(BAR(BAR_ABOK), 1); }
            spin_until(t0);
            mbar_wait(BAR(kc < 7 ? BAR_RG1 + kc : BAR_A7), 1);
            cload(kc);
            t0 = clock32() + (mbar_test(BAR(BAR_ABOK), 1) ? CLD_DT : CE1_DT);
          }
        }
        float s0 = 0.f, q0 = 0.f, s1 = 0.f, q1 = 0.f;
        const int lr = p * 16 + (lane >> 1);
        const uint32_t src = sb + OFF_A + lr * 128 + ((((lane & 1) * 4) ^ (lr & 7)) << 4);
#pragma unroll 1
        for (int k = 0; k < 9; k++) {
          if (k == 3) {
            mbar_wait(BAR(BAR_SENT), layer);
            if (lane == 0) { if (layer * 2 == EVPH) EV(39); cnt_arrive(CNT_X + (layer * 2 * 16 + r) * 9 + 7); if (layer * 2 == EVPH) EV(55); }
            __syncwarp();
          }
          if (k == 3) {
            if (layer == 0) cnt_wait(CNT_CS, ep1 * NHELP);
            float4 cs[5];
#pragma unroll
            for (int i = 0; i < 5; i++) cs[i] = __ldcg(reinterpret_cast<const float4*>(g_cs1 + p * 576) + min(lane + i * 32, 143));
#pragma unroll
            for (int i = 0; i < 5; i++) reinterpret_cast<float4*>(smem + OFF_CS1)[min(lane + i * 32, 143)] = cs[i];
            __syncwarp();
            mbar_arrive_if(BAR(BAR_CSOK), lane == 0);
          }
          if (lane == 0 && layer == 1 && k == 6) EV(31);
          mbar_wait(BAR(BAR_X1F + k), layer);
          if (lane == 0 && layer == 1 && k == 6) EV(30);
          uint4 v[4];
#pragma unroll
          for (int i = 0; i < 4; i++) v[i] = lds128((src ^ (i << 4)) + k * A_SLOT);
          sum8(v[0], s0, q0); sum8(v[1], s1, q1); sum8(v[2], s0, q0); sum8(v[3], s1, q1);
        }
        s0 += s1; q0 += q1;
        s0 += __shfl_xor_sync(0xffffffffu, s0, 1);
        q0 += __shfl_xor_sync(0xffffffffu, q0, 1);
        if (lane == 0 && layer == 1) EV(29);
        if (!(lane & 1)) stat_publish(&g_stat[(layer + 1) * SEQ + myrow], s0, q0, ep1);
        __syncwarp();
        stat_gather(&g_stat[(layer + 1) * SEQ + r * 128 + lane], ep1, reinterpret_cast<float*>(smem + OFF_RS) + lane, nullptr);
        __syncwarp();
        mbar_arrive_if(BAR(BAR_RSOK), lane == 0);
        if (layer == 0) {
          t0 = clock32();
#pragma unroll 1
          for (int i = 0; i < 32; i++) {
            pace(t0, i * CPF2_DT);
            asm volatile("prefetch.global.L2::evict_normal [%0];" ::"l"(cbase + (size_t)(i & 7) * 16 * SEQ * 2 + (i >> 3) * 256));
          }
        }
      }
    }
  } else {
    asm volatile("setmaxnreg.inc.sync.aligned.u32 232;");
    const uint32_t elect = (tid & 127) == 0;
    const uint32_t lane0 = lane == 0;
    if (wg == 1) {
      const int t = tid & 127;
      const int myrow = r * 128 + p * 16 + (t >> 3);
      const uint4* src = reinterpret_cast<const uint4*>(xin + (size_t)myrow * DM) + (t & 7);
      uint4* dst = reinterpret_cast<uint4*>(xout + (size_t)myrow * DM) + (t & 7);
      const int n = r * 9 + min(t >> 3, 8);
      const uint4* dsrc = reinterpret_cast<const uint4*>((m ? dim : dre) + (size_t)((n / 48) * 192 + q * 48 + n % 48) * DM) + (t & 7);
      float s = 0.f, qq = 0.f, sd = 0.f, s2 = 0.f, q2 = 0.f;
      uint4 v[3], d[3], vn[6], dn[6];
#pragma unroll
      for (int i = 0; i < 3; i++) { v[i] = __ldg(src + i * 8); d[i] = __ldg(dsrc + i * 8); }
#pragma unroll
      for (int i = 0; i < 6; i++) { vn[i] = __ldg(src + 24 + i * 8); dn[i] = __ldg(dsrc + 24 + i * 8); }
      START_SYNC();
#pragma unroll 1
      for (int it = 0; it < 72; it += 24) {
        sum8(v[0], s, qq); sum8(v[1], s2, q2); sum8(v[2], s, qq);
#pragma unroll
        for (int i = 0; i < 3; i++) {
          sd += ((bf_lo(d[i].x) + bf_hi(d[i].x)) + (bf_lo(d[i].y) + bf_hi(d[i].y))) + ((bf_lo(d[i].z) + bf_hi(d[i].z)) + (bf_lo(d[i].w) + bf_hi(d[i].w)));
          dst[it + i * 8] = v[i];
          v[i] = vn[i]; d[i] = dn[i]; vn[i] = vn[i + 3]; dn[i] = dn[i + 3];
        }
      }
      s += s2; qq += q2;
#pragma unroll
      for (int o = 1; o < 8; o <<= 1) {
        s += __shfl_xor_sync(0xffffffffu, s, o);
        qq += __shfl_xor_sync(0xffffffffu, qq, o);
        sd += __shfl_xor_sync(0xffffffffu, sd, o);
      }
      mbar_wait(BAR(BAR_EPOCH), 0);
      const uint32_t ep1 = *reinterpret_cast<volatile uint32_t*>(smem + OFF_EPOCH);
      if ((t & 7) == 0) {
        stat_publish(&g_stat[myrow], s, qq, ep1);
        if (t < 72) asm volatile("st.relaxed.gpu.global.u64 [%0], %1;" ::"l"(&g_csd[p * 144 + n]), "l"(((unsigned long long)ep1 << 32) | __float_as_uint(sd)) : "memory");
      }
      if (t < 32) g_rsum[(t >> 4) * SEQ + r * 128 + p * 16 + (t & 15)] = 0.f;
      EVE(118);
      __syncwarp();
      if (lane == 0) cnt_arrive(CNT_XINIT + r);
      asm volatile("bar.sync 2, 128;" ::: "memory");
    }

    const int srow = (lane & 7) + ((lane >> 3) & 1) * 8;
    const int schunk = lane >> 4;
    const int frow = warp * 16 + (lane >> 2);
    const uint32_t bfull = BAR(BAR_BFULL), bempty = BAR(BAR_BEMPTY);
    constexpr uint32_t alo0 = ((sbd + OFF_A) >> 4) | (1u << 16);

#pragma unroll 1
    for (int layer = 0; layer < 2; layer++) {
      auto rowsums = [&](float (&rsum)[4]) {
#pragma unroll
        for (int i = 0; i < 4; i++) {
          rsum[i] += __shfl_xor_sync(0xffffffffu, rsum[i], 1);
          rsum[i] += __shfl_xor_sync(0xffffffffu, rsum[i], 2);
        }
        const int i = lane & 3;
        const float v = i == 0 ? rsum[0] : (i == 1 ? rsum[1] : (i == 2 ? rsum[2] : rsum[3]));
        asm volatile("red.global.add.f32 [%0], %1;" ::"l"(&g_rsum[layer * SEQ + r * 128 + frow + (i & 1) * 8 + (i >> 1) * 64]), "f"(v) : "memory");
      };
      auto flush = [&](auto& acc0, auto& acc1, auto na, int pi, int atom0) {
        constexpr int NA = decltype(na)::value;
        const int ffn = pi >= 7;
        const uint32_t fdone = BAR(BAR_FDONE + ffn * 9 + atom0);
        mbar_wait(BAR(BAR_FOK + ffn), layer);
        constexpr int HOFF = 2048;
        if (atom0) mbar_wait(fdone - 8, layer);
        const uint32_t stg = sb + OFF_STG + warp * 4096;
        const uint32_t sad = stg + srow * 128;
        const uint32_t dt = pi == 10 ? FLUSH_DT_D : (pi == 3 ? FLUSH_DT_C : FLUSH_DT);
        float rs[4];
        if (NA == 3) {
#pragma unroll
          for (int i = 0; i < 4; i++) rs[i] = 0.f;
        } else {
          if (pi < 9) mbar_wait(BAR(BAR_RSOK), layer);
#pragma unroll
          for (int i = 0; i < 4; i++) rs[i] = lds32f(sb + OFF_RS + (frow + (i & 1) * 8 + (i >> 1) * 64) * 4);
        }
        uint32_t tn = clock32() + warp * (dt * STAGGER / 4);
#pragma unroll
        for (int n = 0; n < 2 * NA; n++) {
          uint32_t w[16];
#pragma unroll
          for (int j = 0; j < 16; j++) {
            const int o = (n >> 1) * 32 + j * 2;
            if (NA == 3) {
              w[j] = (n & 1) ? pk(acc1[o], acc1[o + 1]) : pk(acc0[o], acc0[o + 1]);
              rs[(n & 1) * 2 + (j & 1)] += (n & 1) ? acc1[o] + acc1[o + 1] : acc0[o] + acc0[o + 1];
            } else {
              const float f = rs[(n & 1) * 2 + (j & 1)];
              w[j] = (n & 1) ? pk(acc1[o] * f, acc1[o + 1] * f) : pk(acc0[o] * f, acc0[o + 1] * f);
            }
          }
#pragma unroll
          for (int j = 0; j < 4; j++)
            stsm4(sad + (n & 1) * HOFF + (((j * 2 + schunk) ^ (srow & 7)) << 4), w[j * 4], w[j * 4 + 1], w[j * 4 + 2], w[j * 4 + 3]);
          if (NA == 3 && n == 5) rowsums(rs);
          fence_async_smem();
          if (n > FRONT) tn += dt;
          spin_until(tn);
          __syncwarp();
          if (elect_one()) {
            tma_red2d(&maps.xred, stg + (n & 1) * HOFF, (atom0 + (n >> 1)) * 64, r * 128 + (n & 1) * 64 + warp * 16);
            bulk_commit();
            if (n == 2 * NA - 1) {
              bulk_wait0();
              mbar_arrive(fdone + 8 * (NA - 1));
            } else if (n) {
              asm volatile("cp.async.bulk.wait_group 1;" ::: "memory");
              if (!(n & 1)) mbar_arrive(fdone + 8 * ((n >> 1) - 1));
            }
          }
          __syncwarp();
        }
      };
      if (wg == 0) {
        float acc0[72], acc1[72];
        if (layer == 0) { START_SYNC(); TL(0); }
        constexpr uint32_t blo0 = ((sbd + OFF_B) >> 4) | (1u << 16);
        uint32_t ready = 0;
        auto step = [&](int s, auto first) {
          constexpr bool F = decltype(first)::value;
          if (!ready) {
            mbar_wait(BAR(BAR_XF + s), layer);
            mbar_wait(BAR(BAR_DF + s), layer);
            if (F && layer) mbar_wait(BAR(BAR_GO + 15), 0);
          }
          if (F) TL(1 + layer * 36);
          if (layer == 0) EVE(90 + s);
          const uint32_t alo = alo0 + s * (A_SLOT >> 4);
          const uint32_t blo = blo0 + dslot(layer, s) * (D_SLOT >> 4);
          wg_fence();
#pragma unroll
          for (int k = 0; k < 4; k++) {
            if (F && k == 0) {
              wgmma_n144<0, true>(acc0, desc(alo, DESC_HI_128), desc(blo, DESC_HI_128));
              wgmma_n144<0, true>(acc1, desc(alo + 512, DESC_HI_128), desc(blo, DESC_HI_128));
            } else {
              wgmma_n144<0, false>(acc0, desc(alo + k * 2, DESC_HI_128), desc(blo + k * 2, DESC_HI_128));
              wgmma_n144<0, false>(acc1, desc(alo + 512 + k * 2, DESC_HI_128), desc(blo + k * 2, DESC_HI_128));
            }
          }
          wg_commit();
          ready = mbar_test(BAR(BAR_XF + s + 1), layer) & mbar_test(BAR(BAR_DF + min(s + 1, 8)), layer);
          if (!F) {
            wg_wait<1>();
            mbar_arrive_if(BAR(BAR_RG1 - 1 + s), elect);
          }
        };
        step(0, TrueT{});
#pragma unroll 1
        for (int s = 1; s < 9; s++) step(s, FalseT{});
        mbar_arrive_if(BAR(BAR_GO), elect);
        asm volatile("bar.sync %0, 128;" ::"r"(1 + wg) : "memory");
        mbar_wait(BAR(BAR_CSD), 0);
        float2 cd[18];
#pragma unroll
        for (int i = 0; i < 18; i++) cd[i] = lds64f(sb + OFF_CSD + (i * 8 + (lane & 3) * 2) * 4);
        mbar_wait(BAR(BAR_STAT), layer);
        const float sg = m ? -1.f : 1.f;
        float2 st[4];
#pragma unroll
        for (int i = 0; i < 4; i++) {
          st[i].x = lds32f(sb + OFF_RS + (frow + (i & 1) * 8 + (i >> 1) * 64) * 4) * sg;
          st[i].y = lds32f(sb + OFF_MEAN + (frow + (i & 1) * 8 + (i >> 1) * 64) * 4);
        }
        wg_wait<0>();
        reg_fence(acc0); reg_fence(acc1);
        TL(2 + layer * 36);
        const uint32_t stg = sb + (warp * 16 + srow) * 96 + schunk * 16;
#pragma unroll
        for (int b2 = 0; b2 < 9; b2++) {
          const float2 c0 = cd[b2 * 2], c1 = cd[b2 * 2 + 1];
          const uint32_t ad = stg + (b2 < 3 ? OFF_STG : OFF_A + (6 + b2 / 3) * A_SLOT) + (b2 % 3) * 32;
          const int o = b2 * 8;
          stsm4(ad,
                pk(fmaf(c0.x, st[0].y, acc0[o]) * st[0].x, fmaf(c0.y, st[0].y, acc0[o + 1]) * st[0].x),
                pk(fmaf(c0.x, st[1].y, acc0[o + 2]) * st[1].x, fmaf(c0.y, st[1].y, acc0[o + 3]) * st[1].x),
                pk(fmaf(c1.x, st[0].y, acc0[o + 4]) * st[0].x, fmaf(c1.y, st[0].y, acc0[o + 5]) * st[0].x),
                pk(fmaf(c1.x, st[1].y, acc0[o + 6]) * st[1].x, fmaf(c1.y, st[1].y, acc0[o + 7]) * st[1].x));
          stsm4(ad + 64 * 96,
                pk(fmaf(c0.x, st[2].y, acc1[o]) * st[2].x, fmaf(c0.y, st[2].y, acc1[o + 1]) * st[2].x),
                pk(fmaf(c0.x, st[3].y, acc1[o + 2]) * st[3].x, fmaf(c0.y, st[3].y, acc1[o + 3]) * st[3].x),
                pk(fmaf(c1.x, st[2].y, acc1[o + 4]) * st[2].x, fmaf(c1.y, st[2].y, acc1[o + 5]) * st[2].x),
                pk(fmaf(c1.x, st[3].y, acc1[o + 6]) * st[3].x, fmaf(c1.y, st[3].y, acc1[o + 7]) * st[3].x));
          if (b2 == 2 || b2 == 8) {
            fence_async_smem();
            __syncwarp();
            mbar_arrive_if(BAR(BAR_ABSTG + (b2 == 8)), lane0);
          }
          if (b2 == 2) {
            asm volatile("bar.sync %0, 128;" ::"r"(1 + wg) : "memory");
            mbar_arrive_if(BAR(BAR_RG1 + 8), elect);
#pragma unroll
            for (int i = 0; i < NB; i++) mbar_arrive_if(BAR(BAR_BEMPTY + i), elect);
          }
        }
        TL(3 + layer * 36);
      }
#pragma unroll 1
      for (int pi = 2 - wg; pi < 12; pi += 2) {
        if (pi < 7) {
          float acc0[96], acc1[96];
          int atom0;
          int seq, nt, nt2 = 0, nt3 = 0, gap = 0, gap2 = 0, fbar, rbar = BAR_RNONE, sgm = pi;
          if (pi < 4) { atom0 = (pi - 1) * 3; nt = 8; seq = pi * 16 - 11; fbar = BAR_CF; if (pi == 3) rbar = BAR_RG2; }
          else if (pi == 4) { atom0 = 0; seq = 53; nt = G3A_C1 / 2; nt2 = (G3A_C2 - G3A_C1) / 2; nt3 = 9 - G3A_C2 / 2; gap = G3B_C1; gap2 = G3B_C2 - G3B_C1; fbar = BAR_X1F; }
          else if (pi == 5) { atom0 = 3; seq = 53 + G3A_C1; nt = G3B_C1 / 2; nt2 = (G3B_C2 - G3B_C1) / 2; nt3 = 9 - G3B_C2 / 2; gap = G3A_C2 - G3A_C1; gap2 = 18 - G3A_C2; fbar = BAR_X1F; rbar = BAR_RG3B; }
          else { atom0 = 6; seq = 89; nt = 9; fbar = BAR_X1F + 3; rbar = BAR_RG3C; sgm = 10; }
          constexpr uint32_t blo0 = ((sbd + OFF_B) >> 4) | ((4096u >> 4) << 16);
          seq += layer * LSTEPS;
          uint32_t so = (seq % NB) * 8, ph = seq / NB;
          uint32_t alo = alo0 + ((pi == 6) ? 6 * (A_SLOT >> 4) : 0);
          uint32_t fa = BAR(fbar), ra = BAR(rbar), go = BAR(BAR_GO + sgm);
          uint32_t pso, rel, epok = 0;
          auto issue = [&](uint32_t a, auto first) {
            constexpr bool F = decltype(first)::value;
            const uint32_t blo = blo0 + so * (B_SLOT >> 7);
            wg_fence();
            wgmma_n192<1, F>(acc0, desc(a, DESC_HI_128), desc(blo, DESC_HI_128));
            wgmma_n192<1, F>(acc1, desc(a + 512, DESC_HI_128), desc(blo, DESC_HI_128));
            wgmma_n192<1, false>(acc0, desc(a + 2, DESC_HI_128), desc(blo + 128, DESC_HI_128));
            wgmma_n192<1, false>(acc1, desc(a + 514, DESC_HI_128), desc(blo + 128, DESC_HI_128));
            wg_commit();
          };
          auto advance = [&]() { so += 8; if (so == NB * 8) { so = 0; ph++; } };
          auto enter = [&]() {
            const uint32_t t0 = mbar_test(fa, layer), t1 = mbar_test(go - 8, layer), t2 = mbar_test(bfull + so, ph);
            if (!(t0 & t1 & t2)) {
              mbar_wait(fa, layer);
              mbar_wait(go - 8, layer);
              mbar_wait(bfull + so, ph);
            }
          };
          enter();
          TL(1 + pi * 3 + layer * 36);
          issue(alo, TrueT{});
          pso = so;
          advance();
          mbar_wait(bfull + so, ph);
#pragma unroll 1
          for (;;) {
            issue(alo + 4, FalseT{});
            const uint32_t cso = so;
            advance();
            alo += A_SLOT >> 4;
            if (alo == alo0 + 9 * (A_SLOT >> 4)) alo = alo0 + 3 * (A_SLOT >> 4);
            fa += 8;
            if (--nt == 0) {
              mbar_arrive_if(go, elect);
              wg_wait<1>();
              mbar_arrive_if(bempty + pso, elect);
              if (nt2 == 0 && pi >= 4) {
                const uint32_t t0 = mbar_test(BAR(BAR_STAT + 1), layer), t1 = mbar_test(BAR(BAR_CSOK), layer), t2 = mbar_test(BAR(BAR_RG3B + 2), layer);
                epok = t0 & t1 & t2;
              }
              wg_wait<0>();
              mbar_arrive_if(bempty + cso, elect);
              mbar_arrive_if(ra, elect);
              if (nt2 == 0) break;
              nt = nt2; nt2 = nt3; nt3 = 0;
              const uint32_t t = so + gap * 8;
              so = t % (NB * 8); ph += t / (NB * 8);
              gap = gap2;
              go += 16;
              rel = 0;
              enter();
            } else {
              const uint32_t ready = mbar_test(fa, layer) & mbar_test(bfull + so, ph);
              wg_wait<1>();
              mbar_arrive_if(bempty + pso, elect);
              rel = elect;
              if (!ready) {
                mbar_wait(fa, layer);
                mbar_wait(bfull + so, ph);
              }
            }
            issue(alo, FalseT{});
            pso = so;
            advance();
            const uint32_t ready = mbar_test(bfull + so, ph);
            wg_wait<1>();
            mbar_arrive_if(bempty + cso, rel);
            mbar_arrive_if(ra, rel);
            ra += 8;
            if (!ready) {
              mbar_wait(bfull + so, ph);
            }
          }
        wg_wait<0>();
        reg_fence(acc0); reg_fence(acc1);
        TL(2 + pi * 3 + layer * 36);
        if (pi >= 4 && pi <= 6) {
          if (!epok) {
            mbar_wait(BAR(BAR_STAT + 1), layer);
            mbar_wait(BAR(BAR_CSOK), layer);
            mbar_wait(BAR(BAR_RG3B + 2), layer);
          }
          if (pi == 6) asm volatile("bar.sync %0, 128;" ::"r"(1 + wg) : "memory");
          float2 st[4];
#pragma unroll
          for (int i = 0; i < 4; i++) st[i].y = lds32f(sb + OFF_MEAN + (frow + (i & 1) * 8 + (i >> 1) * 64) * 4);
          const uint32_t cs = sb + OFF_CS1 + (atom0 * 64 + (lane & 3) * 2) * 4;
          const uint32_t dst = sb + OFF_A + atom0 * A_SLOT + (warp * 16 + srow) * 128;
          float2 cn[2][2];
          cn[0][0] = lds64f(cs); cn[0][1] = lds64f(cs + 32); cn[1][0] = lds64f(cs + 64); cn[1][1] = lds64f(cs + 96);
#pragma unroll
          for (int b2 = 0; b2 < 12; b2++) {
            if ((b2 & 3) == 0 && pi == 5) mbar_wait(BAR(BAR_RG3C + 3 + (b2 >> 2)), layer);
            const float2 c0 = cn[b2 & 1][0], c1 = cn[b2 & 1][1];
            if (b2 + 2 < 12) { cn[b2 & 1][0] = lds64f(cs + (b2 + 2) * 64); cn[b2 & 1][1] = lds64f(cs + (b2 + 2) * 64 + 32); }
            const uint32_t ad = dst + (b2 >> 2) * A_SLOT + ((((b2 & 3) * 2 + schunk) ^ (srow & 7)) << 4);
            const int o = b2 * 8;
            stsm4(ad,
                  pk_relu(fmaf(c0.x, st[0].y, acc0[o]), fmaf(c0.y, st[0].y, acc0[o + 1])),
                  pk_relu(fmaf(c0.x, st[1].y, acc0[o + 2]), fmaf(c0.y, st[1].y, acc0[o + 3])),
                  pk_relu(fmaf(c1.x, st[0].y, acc0[o + 4]), fmaf(c1.y, st[0].y, acc0[o + 5])),
                  pk_relu(fmaf(c1.x, st[1].y, acc0[o + 6]), fmaf(c1.y, st[1].y, acc0[o + 7])));
            stsm4(ad + 8192,
                  pk_relu(fmaf(c0.x, st[2].y, acc1[o]), fmaf(c0.y, st[2].y, acc1[o + 1])),
                  pk_relu(fmaf(c0.x, st[3].y, acc1[o + 2]), fmaf(c0.y, st[3].y, acc1[o + 3])),
                  pk_relu(fmaf(c1.x, st[2].y, acc1[o + 4]), fmaf(c1.y, st[2].y, acc1[o + 5])),
                  pk_relu(fmaf(c1.x, st[3].y, acc1[o + 6]), fmaf(c1.y, st[3].y, acc1[o + 7])));
            if ((b2 & 3) == 3 && (pi == 6 || b2 == 11)) {
              fence_async_smem();
              __syncwarp();
              mbar_arrive_if(BAR(BAR_HF + atom0 + (b2 >> 2)), lane0);
              if (b2 == 11 && pi != 6) { mbar_arrive_if(BAR(BAR_HF + atom0), lane0); mbar_arrive_if(BAR(BAR_HF + atom0 + 1), lane0); }
            }
          }
        } else if (pi == 3) {
          asm volatile("bar.sync %0, 128;" ::"r"(1 + wg) : "memory");
          const uint32_t dst = sb + OFF_A + 6 * A_SLOT + (warp * 16 + srow) * 128;
          float rs[4] = {0.f, 0.f, 0.f, 0.f};
#pragma unroll
          for (int b2 = 0; b2 < 12; b2++) {
            const uint32_t ad = dst + (b2 >> 2) * A_SLOT + ((((b2 & 3) * 2 + schunk) ^ (srow & 7)) << 4);
            const int o = b2 * 8;
            stsm4(ad, pk(acc0[o], acc0[o + 1]), pk(acc0[o + 2], acc0[o + 3]), pk(acc0[o + 4], acc0[o + 5]), pk(acc0[o + 6], acc0[o + 7]));
            stsm4(ad + 8192, pk(acc1[o], acc1[o + 1]), pk(acc1[o + 2], acc1[o + 3]), pk(acc1[o + 4], acc1[o + 5]), pk(acc1[o + 6], acc1[o + 7]));
            rs[0] += (acc0[o] + acc0[o + 1]) + (acc0[o + 4] + acc0[o + 5]);
            rs[1] += (acc0[o + 2] + acc0[o + 3]) + (acc0[o + 6] + acc0[o + 7]);
            rs[2] += (acc1[o] + acc1[o + 1]) + (acc1[o + 4] + acc1[o + 5]);
            rs[3] += (acc1[o + 2] + acc1[o + 3]) + (acc1[o + 6] + acc1[o + 7]);
            if ((b2 & 3) == 3) {
              fence_async_smem();
              __syncwarp();
              if (b2 == 3) {
                if (lane0) {
                  tma_red2d(&maps.xred, sb + OFF_A + 6 * A_SLOT + warp * 2048, 384, r * 128 + warp * 16);
                  tma_red2d(&maps.xred, sb + OFF_A + 6 * A_SLOT + 8192 + warp * 2048, 384, r * 128 + 64 + warp * 16);
                  bulk_commit();
                }
              } else {
                mbar_arrive_if(BAR(BAR_FDONE + 6 + (b2 >> 2)), lane0);
              }
            }
          }
          rowsums(rs);
          bulk_wait0();
          __syncwarp();
          mbar_arrive_if(BAR(BAR_FDONE + 6), lane0);
        } else {
          flush(acc0, acc1, IntT<3>{}, pi, atom0);
        }
        } else {
          auto hpass = [&](auto na) {
            constexpr int NA = decltype(na)::value, KU = 6 / NA, NS = 36 / KU;
            float a0[64], a1[NA == 2 ? 64 : 1];
            constexpr uint32_t blo0 = ((sbd + OFF_B) >> 4) | ((6144u >> 4) << 16);
            const int seq = 23 + pi * 12 + layer * LSTEPS;
            uint32_t so = (seq % NB) * 8, ph = seq / NB, pso = 0;
            uint32_t ready = 0;
            auto step = [&](int s, auto first) {
              constexpr bool F = decltype(first)::value;
              if (F) {
                const uint32_t t0 = mbar_test(BAR(BAR_HF), layer), t1 = mbar_test(BAR(BAR_GO + 3 + pi), layer), t2 = mbar_test(bfull + so, ph);
                ready = t0 & t1 & t2;
              }
              if (!ready) {
                if (NA == 2) mbar_wait(BAR(BAR_HF + ((s * KU + KU - 1) >> 2)), layer);
                if (F) mbar_wait(BAR(BAR_GO + 3 + pi), layer);
                mbar_wait(bfull + so, ph);
              }
              if (F) TL(1 + pi * 3 + layer * 36);
              const uint32_t blo = blo0 + so * (B_SLOT >> 7);
              wg_fence();
#pragma unroll
              for (int j = 0; j < KU; j++) {
                const int u = s * KU + j;
                const uint64_t da0 = desc(alo0 + (u >> 2) * (A_SLOT >> 4) + (u & 3) * 2, DESC_HI_128);
                const uint64_t da1 = desc(alo0 + (u >> 2) * (A_SLOT >> 4) + (u & 3) * 2 + 512, DESC_HI_128);
                const uint64_t db = desc(blo + j * 128, DESC_HI_128);
                if constexpr (NA == 2) {
                  if (F && j == 0) { wgmma_n128<1, true>(a0, da0, db); wgmma_n128<1, true>(a1, da1, db); }
                  else { wgmma_n128<1, false>(a0, da0, db); wgmma_n128<1, false>(a1, da1, db); }
                } else {
                  if (F && j == 0) wgmma_n128<0, true, 1>(a0, db, da0);
                  else wgmma_n128<0, false, 1>(a0, db, da0);
                }
              }
              wg_commit();
              const uint32_t cso = so;
              so += 8;
              if (so == NB * 8) { so = 0; ph++; }
              mbar_arrive_if(BAR(BAR_GO + 4 + pi), elect && s == NS - 1);
              ready = mbar_test(bfull + so, ph);
              if (NA == 2) ready &= mbar_test(BAR(BAR_HF + ((s * KU + 2 * KU - 1) >> 2)), layer);
              if (!F) {
                wg_wait<1>();
                mbar_arrive_if(bempty + pso, elect);
                if (NA == 1) {
                  mbar_arrive_if(BAR(BAR_RG4 - 1 + ((6 * s) >> 2)), elect);
                  mbar_arrive_if(BAR(BAR_RG4 - 2 + ((6 * s) >> 2)), elect && !(s & 1));
                }
              }
              pso = cso;
            };
            float2 rsv[NA == 1 ? 16 : 1];
            if constexpr (NA == 1) {
#pragma unroll
              for (int i = 0; i < 16; i++) rsv[i] = lds64f(sb + OFF_RS + (i * 8 + (lane & 3) * 2) * 4);
            }
            step(0, TrueT{});
#pragma unroll 1
            for (int s = 1; s < NS; s++) step(s, FalseT{});
            wg_wait<0>();
            mbar_arrive_if(bempty + pso, elect);
            if (NA == 1) { mbar_arrive_if(BAR(BAR_RG4 + 7), elect); mbar_arrive_if(BAR(BAR_RG4 + 8), elect); }
            reg_fence(a0);
            TL(2 + pi * 3 + layer * 36);
            if constexpr (NA == 2) {
              reg_fence(a1);
              flush(a0, a1, na, pi, (pi - 7) * 2);
            } else {
              asm volatile("bar.sync %0, 128;" ::"r"(1 + wg) : "memory");
              const uint32_t tb = sb + OFF_A + 8 * A_SLOT;
              const uint32_t ad = tb + ((lane >> 4) * 8 + (lane & 7)) * 128 + (((warp * 2 + ((lane >> 3) & 1)) ^ (lane & 7)) << 4);
#pragma unroll
              for (int b2 = 0; b2 < 8; b2++) {
                const float2 f0 = rsv[b2 * 2], f1 = rsv[b2 * 2 + 1];
                const int o = b2 * 8;
                asm volatile("stmatrix.sync.aligned.m8n8.x4.trans.shared.b16 [%0], {%1,%2,%3,%4};" ::"r"(ad + b2 * 2048),
                             "r"(pk(a0[o] * f0.x, a0[o + 1] * f0.y)), "r"(pk(a0[o + 2] * f0.x, a0[o + 3] * f0.y)),
                             "r"(pk(a0[o + 4] * f1.x, a0[o + 5] * f1.y)), "r"(pk(a0[o + 6] * f1.x, a0[o + 7] * f1.y)));
              }
              fence_async_smem();
              __syncwarp();
              mbar_arrive_if(BAR(BAR_FDONE + 17), lane0);
              if (layer == 0) {
                const int row = tid & 127;
                const uint32_t ra = sb + OFF_A + row * 128 + ((row & 7) << 4);
                float s0 = 0.f, q0 = 0.f, s1 = 0.f, q1 = 0.f;
#pragma unroll 1
                for (int k = 0; k < 9; k++) {
                  mbar_wait(BAR(BAR_XF + k), 1);
                  uint4 v[8];
#pragma unroll
                  for (int i = 0; i < 8; i++) v[i] = lds128((ra ^ (i << 4)) + k * A_SLOT);
#pragma unroll
                  for (int i = 0; i < 8; i += 2) { sum8(v[i], s0, q0); sum8(v[i + 1], s1, q1); }
                  if (k == CE1 - 1) {
                    asm volatile("bar.sync %0, 128;" ::"r"(1 + wg) : "memory");
                    mbar_arrive_if(BAR(BAR_S6), elect);
                  }
                }
                const float mean = (s0 + s1) * (1.0f / DM);
                reinterpret_cast<float*>(smem + OFF_RS)[row] = rsqrtf(fmaxf((q0 + q1) * (1.0f / DM) - mean * mean, 0.f) + 1e-5f);
                reinterpret_cast<float*>(smem + OFF_MEAN)[row] = -mean;
                asm volatile("bar.sync %0, 128;" ::"r"(1 + wg) : "memory");
                mbar_arrive_if(BAR(BAR_STAT), elect);
                EVE(25);
              }
            }
          };
          if (pi < 11) hpass(IntT<2>{}); else hpass(IntT<1>{});
        }
        TL(3 + pi * 3 + layer * 36);
      }
    }
  }
#undef BAR
}

typedef CUresult (*EncodeFn)(CUtensorMap*, CUtensorMapDataType, cuuint32_t, void*, const cuuint64_t*, const cuuint64_t*, const cuuint32_t*,
                             const cuuint32_t*, CUtensorMapInterleave, CUtensorMapSwizzle, CUtensorMapL2promotion, CUtensorMapFloatOOBfill);

void make2d(EncodeFn enc, CUtensorMap* m, const void* ptr, uint64_t inner, uint64_t outer, uint32_t bi, uint32_t bo, CUtensorMapSwizzle sw) {
  cuuint64_t d[2] = {inner, outer};
  cuuint64_t s[1] = {inner * 2};
  cuuint32_t b[2] = {bi, bo}, e[2] = {1, 1};
  enc(m, CU_TENSOR_MAP_DATA_TYPE_BFLOAT16, 2, const_cast<void*>(ptr), d, s, b, e, CU_TENSOR_MAP_INTERLEAVE_NONE, sw,
      CU_TENSOR_MAP_L2_PROMOTION_L2_128B, CU_TENSOR_MAP_FLOAT_OOB_FILL_NONE);
}
void make3d(EncodeFn enc, CUtensorMap* m, const void* ptr, uint64_t d0, uint64_t d1, uint64_t d2, uint64_t s1, uint64_t s2,
            uint32_t b0, uint32_t b1, uint32_t b2, CUtensorMapSwizzle sw) {
  cuuint64_t d[3] = {d0, d1, d2};
  cuuint64_t s[2] = {s1, s2};
  cuuint32_t b[3] = {b0, b1, b2}, e[3] = {1, 1, 1};
  enc(m, CU_TENSOR_MAP_DATA_TYPE_BFLOAT16, 3, const_cast<void*>(ptr), d, s, b, e, CU_TENSOR_MAP_INTERLEAVE_NONE, sw,
      CU_TENSOR_MAP_L2_PROMOTION_L2_128B, CU_TENSOR_MAP_FLOAT_OOB_FILL_NONE);
}

}

extern "C" void kernel_launch(void* const* d_in, const int* in_sizes, int n_in, void* d_out, int out_size) {
  (void)in_sizes; (void)n_in; (void)out_size;
  const __nv_bfloat16* x = (const __nv_bfloat16*)d_in[0];
  const __nv_bfloat16* cr = (const __nv_bfloat16*)d_in[1];
  const __nv_bfloat16* ci = (const __nv_bfloat16*)d_in[2];
  const __nv_bfloat16* dr = (const __nv_bfloat16*)d_in[3];
  const __nv_bfloat16* di = (const __nv_bfloat16*)d_in[4];
  const __nv_bfloat16* w1 = (const __nv_bfloat16*)d_in[6];
  const __nv_bfloat16* w2 = (const __nv_bfloat16*)d_in[7];
  __nv_bfloat16* out = (__nv_bfloat16*)d_out;

  void* fn = nullptr;
  cudaDriverEntryPointQueryResult qr;
  cudaGetDriverEntryPoint("cuTensorMapEncodeTiled", &fn, cudaEnableDefault, &qr);
  EncodeFn enc = (EncodeFn)fn;
  void* ab = nullptr;
  cudaGetSymbolAddress(&ab, g_ab);

  Maps maps;
  make2d(enc, &maps.xin, x, DM, SEQ, 64, 128, CU_TENSOR_MAP_SWIZZLE_128B);
  make2d(enc, &maps.xld, out, DM, SEQ, 64, 128, CU_TENSOR_MAP_SWIZZLE_128B);
  make2d(enc, &maps.xred, out, DM, SEQ, 64, 16, CU_TENSOR_MAP_SWIZZLE_128B);
  make2d(enc, &maps.cr, cr, SEQ, SEQ, 64, 128, CU_TENSOR_MAP_SWIZZLE_128B);
  make2d(enc, &maps.ci, ci, SEQ, SEQ, 64, 128, CU_TENSOR_MAP_SWIZZLE_128B);
  make3d(enc, &maps.dr, dr, DM, 192, 3, DM * 2, 192 * DM * 2, 64, 48, 3, CU_TENSOR_MAP_SWIZZLE_128B);
  make3d(enc, &maps.di, di, DM, 192, 3, DM * 2, 192 * DM * 2, 64, 48, 3, CU_TENSOR_MAP_SWIZZLE_128B);
  make3d(enc, &maps.abld, ab, 64, 4 * SEQ, DM / 64, DM * 2, 128, 64, 32, 3, CU_TENSOR_MAP_SWIZZLE_128B);
  make2d(enc, &maps.abst, ab, DM, 4 * SEQ, 48, 128, CU_TENSOR_MAP_SWIZZLE_NONE);
  make3d(enc, &maps.w1, w1, 64, DM, DFF / 64, DFF * 2, 128, 64, 32, 3, CU_TENSOR_MAP_SWIZZLE_128B);
  make3d(enc, &maps.w2, w2, 64, DFF, DM / 64, DM * 2, 128, 64, 48, 2, CU_TENSOR_MAP_SWIZZLE_128B);
  make3d(enc, &maps.w2n, w2, 64, DFF, DM / 64, DM * 2, 128, 64, 96, 1, CU_TENSOR_MAP_SWIZZLE_128B);

  cudaFuncSetAttribute(fnet_ffn_kernel, cudaFuncAttributeMaxDynamicSharedMemorySize, SMEM_BYTES);
  cudaLaunchConfig_t cfg = {};
  cfg.gridDim = dim3(NGRID);
  cfg.blockDim = dim3(384);
  cfg.dynamicSmemBytes = SMEM_BYTES;
  cfg.stream = cudaStreamPerThread;
  cudaLaunchAttribute at[1];
  at[0].id = cudaLaunchAttributeClusterDimension;
  at[0].val.clusterDim.x = CLUSTER; at[0].val.clusterDim.y = 1; at[0].val.clusterDim.z = 1;
  cfg.attrs = at;
  cfg.numAttrs = 1;
  cudaLaunchKernelEx(&cfg, fnet_ffn_kernel, maps, x, cr, ci, dr, di, w1, w2, out);
}
```

```cpp
#include <cuda_runtime.h>
#include <cuda_bf16.h>
#include <cuda.h>
#include <stdint.h>

namespace {

constexpr int SEQ = 2048, DM = 576, DFF = 4608;
constexpr int NHELP = 4, NWORK = 128, NGRID = NHELP + NWORK;

constexpr int A_SLOT = 16384, B_SLOT = 12288, NB = 5, D_SLOT = 18432;
constexpr int OFF_A = 0;
constexpr int OFF_B = 9 * A_SLOT;
constexpr int OFF_STG = OFF_B + NB * B_SLOT;
constexpr int OFF_CS1 = OFF_STG + 12288;
constexpr int OFF_CSD = OFF_STG + 16384;
constexpr int OFF_EPOCH = OFF_CSD + 576;
constexpr int OFF_RS = OFF_CSD + 640;
constexpr int OFF_BAR = OFF_RS + 512;
constexpr int SMEM_BYTES = 232448;

constexpr int BAR_HF = 0  , BAR_ABSTG = 9  , BAR_FDONE = 11  ,
              BAR_BEMPTY = 32  , BAR_DREL = 38  , BAR_STGF = 46, BAR_STG2 = 47,
              BAR_CF = 48  , BAR_X1F = 56  ,
              BAR_RG1 = 68, BAR_RG2 = 77, BAR_RG3B = 86, BAR_RG3C = 95, BAR_RG4 = 104, BAR_RNONE = 113  ,
              BAR_STAT = 122  , BAR_FOK = 124  , BAR_EPOCH = 126, BAR_CSD = 127,
              BAR_XF = 128  , BAR_DF = 137  , BAR_ABOK = 146  , BAR_GO = 150  , BAR_XOK = 166  , BAR_SENT = 172,
              BAR_RSOK = 173, BAR_CSOK = 174, BAR_A7 = 175, BAR_RD = 176  , BAR_REL8 = 182, BAR_BFULL = 183  , BAR_A8 = 189, BAR_AB1 = 190, BAR_XRD = 191, NBAR = 192;
constexpr int OFF_MEAN = OFF_BAR + NBAR * 8;
static_assert(OFF_MEAN + 512 <= SMEM_BYTES, "smem");

constexpr int CNT_STRIDE = 32;
constexpr int CNT_AB = 0;
constexpr int CNT_X = 192;
constexpr int CNT_XINIT = CNT_X + 432;
constexpr int CNT_G3 = CNT_XINIT + 16;
constexpr int CNT_CS = CNT_G3 + 32;
constexpr int CNT_TICKET = CNT_CS + 1;
constexpr int NCNT = CNT_TICKET + 1;

__device__ uint32_t g_cnt[NCNT * CNT_STRIDE];
__device__ __nv_bfloat16 g_ab[2 * 2 * SEQ * DM];
__device__ float g_cs1[DFF];
__device__ __align__(16) float g_rsum[2 * SEQ];
__device__ __align__(16) unsigned long long g_csd[8 * 144];
__device__ ulonglong2 g_stat[3 * SEQ];
#define TL(i)
#define EV(i)
#define EVE(i)

template <int V> struct IntT { static constexpr int value = V; };
struct TrueT { static constexpr bool value = true; };
struct FalseT { static constexpr bool value = false; };

struct Maps {
  CUtensorMap xin, xld, xred, cr, ci, dr, di, abld, abst, w1, w2, w2n;
};

template<int TB, bool FIRST, int TA = 0> __device__ __forceinline__ void wgmma_n128(float (&d)[64], uint64_t da, uint64_t db){
  if (FIRST) {
    asm volatile("wgmma.mma_async.sync.aligned.m64n128k16.f32.bf16.bf16 {%0, %1, %2, %3, %4, %5, %6, %7, %8, %9, %10, %11, %12, %13, %14, %15, %16, %17, %18, %19, %20, %21, %22, %23, %24, %25, %26, %27, %28, %29, %30, %31, %32, %33, %34, %35, %36, %37, %38, %39, %40, %41, %42, %43, %44, %45, %46, %47, %48, %49, %50, %51, %52, %53, %54, %55, %56, %57, %58, %59, %60, %61, %62, %63}, %64, %65, 0, 1, 1, %67, %66;"
     : "=f"(d[0]), "=f"(d[1]), "=f"(d[2]), "=f"(d[3]), "=f"(d[4]), "=f"(d[5]), "=f"(d[6]), "=f"(d[7]), "=f"(d[8]), "=f"(d[9]), "=f"(d[10]), "=f"(d[11]), "=f"(d[12]), "=f"(d[13]), "=f"(d[14]), "=f"(d[15]), "=f"(d[16]), "=f"(d[17]), "=f"(d[18]), "=f"(d[19]), "=f"(d[20]), "=f"(d[21]), "=f"(d[22]), "=f"(d[23]), "=f"(d[24]), "=f"(d[25]), "=f"(d[26]), "=f"(d[27]), "=f"(d[28]), "=f"(d[29]), "=f"(d[30]), "=f"(d[31]), "=f"(d[32]), "=f"(d[33]), "=f"(d[34]), "=f"(d[35]), "=f"(d[36]), "=f"(d[37]), "=f"(d[38]), "=f"(d[39]), "=f"(d[40]), "=f"(d[41]), "=f"(d[42]), "=f"(d[43]), "=f"(d[44]), "=f"(d[45]), "=f"(d[46]), "=f"(d[47]), "=f"(d[48]), "=f"(d[49]), "=f"(d[50]), "=f"(d[51]), "=f"(d[52]), "=f"(d[53]), "=f"(d[54]), "=f"(d[55]), "=f"(d[56]), "=f"(d[57]), "=f"(d[58]), "=f"(d[59]), "=f"(d[60]), "=f"(d[61]), "=f"(d[62]), "=f"(d[63])
     : "l"(da), "l"(db), "n"(TB), "n"(TA));
  } else {
    asm volatile("wgmma.mma_async.sync.aligned.m64n128k16.f32.bf16.bf16 {%0, %1, %2, %3, %4, %5, %6, %7, %8, %9, %10, %11, %12, %13, %14, %15, %16, %17, %18, %19, %20, %21, %22, %23, %24, %25, %26, %27, %28, %29, %30, %31, %32, %33, %34, %35, %36, %37, %38, %39, %40, %41, %42, %43, %44, %45, %46, %47, %48, %49, %50, %51, %52, %53, %54, %55, %56, %57, %58, %59, %60, %61, %62, %63}, %64, %65, 1, 1, 1, %67, %66;"
     : "+f"(d[0]), "+f"(d[1]), "+f"(d[2]), "+f"(d[3]), "+f"(d[4]), "+f"(d[5]), "+f"(d[6]), "+f"(d[7]), "+f"(d[8]), "+f"(d[9]), "+f"(d[10]), "+f"(d[11]), "+f"(d[12]), "+f"(d[13]), "+f"(d[14]), "+f"(d[15]), "+f"(d[16]), "+f"(d[17]), "+f"(d[18]), "+f"(d[19]), "+f"(d[20]), "+f"(d[21]), "+f"(d[22]), "+f"(d[23]), "+f"(d[24]), "+f"(d[25]), "+f"(d[26]), "+f"(d[27]), "+f"(d[28]), "+f"(d[29]), "+f"(d[30]), "+f"(d[31]), "+f"(d[32]), "+f"(d[33]), "+f"(d[34]), "+f"(d[35]), "+f"(d[36]), "+f"(d[37]), "+f"(d[38]), "+f"(d[39]), "+f"(d[40]), "+f"(d[41]), "+f"(d[42]), "+f"(d[43]), "+f"(d[44]), "+f"(d[45]), "+f"(d[46]), "+f"(d[47]), "+f"(d[48]), "+f"(d[49]), "+f"(d[50]), "+f"(d[51]), "+f"(d[52]), "+f"(d[53]), "+f"(d[54]), "+f"(d[55]), "+f"(d[56]), "+f"(d[57]), "+f"(d[58]), "+f"(d[59]), "+f"(d[60]), "+f"(d[61]), "+f"(d[62]), "+f"(d[63])
     : "l"(da), "l"(db), "n"(TB), "n"(TA));
  }
}
template<int TB, bool FIRST, int TA = 0> __device__ __forceinline__ void wgmma_n144(float (&d)[72], uint64_t da, uint64_t db){
  if (FIRST) {
    asm volatile("wgmma.mma_async.sync.aligned.m64n144k16.f32.bf16.bf16 {%0, %1, %2, %3, %4, %5, %6, %7, %8, %9, %10, %11, %12, %13, %14, %15, %16, %17, %18, %19, %20, %21, %22, %23, %24, %25, %26, %27, %28, %29, %30, %31, %32, %33, %34, %35, %36, %37, %38, %39, %40, %41, %42, %43, %44, %45, %46, %47, %48, %49, %50, %51, %52, %53, %54, %55, %56, %57, %58, %59, %60, %61, %62, %63, %64, %65, %66, %67, %68, %69, %70, %71}, %72, %73, 0, 1, 1, %75, %74;"
     : "=f"(d[0]), "=f"(d[1]), "=f"(d[2]), "=f"(d[3]), "=f"(d[4]), "=f"(d[5]), "=f"(d[6]), "=f"(d[7]), "=f"(d[8]), "=f"(d[9]), "=f"(d[10]), "=f"(d[11]), "=f"(d[12]), "=f"(d[13]), "=f"(d[14]), "=f"(d[15]), "=f"(d[16]), "=f"(d[17]), "=f"(d[18]), "=f"(d[19]), "=f"(d[20]), "=f"(d[21]), "=f"(d[22]), "=f"(d[23]), "=f"(d[24]), "=f"(d[25]), "=f"(d[26]), "=f"(d[27]), "=f"(d[28]), "=f"(d[29]), "=f"(d[30]), "=f"(d[31]), "=f"(d[32]), "=f"(d[33]), "=f"(d[34]), "=f"(d[35]), "=f"(d[36]), "=f"(d[37]), "=f"(d[38]), "=f"(d[39]), "=f"(d[40]), "=f"(d[41]), "=f"(d[42]), "=f"(d[43]), "=f"(d[44]), "=f"(d[45]), "=f"(d[46]), "=f"(d[47]), "=f"(d[48]), "=f"(d[49]), "=f"(d[50]), "=f"(d[51]), "=f"(d[52]), "=f"(d[53]), "=f"(d[54]), "=f"(d[55]), "=f"(d[56]), "=f"(d[57]), "=f"(d[58]), "=f"(d[59]), "=f"(d[60]), "=f"(d[61]), "=f"(d[62]), "=f"(d[63]), "=f"(d[64]), "=f"(d[65]), "=f"(d[66]), "=f"(d[67]), "=f"(d[68]), "=f"(d[69]), "=f"(d[70]), "=f"(d[71])
     : "l"(da), "l"(db), "n"(TB), "n"(TA));
  } else {
    asm volatile("wgmma.mma_async.sync.aligned.m64n144k16.f32.bf16.bf16 {%0, %1, %2, %3, %4, %5, %6, %7, %8, %9, %10, %11, %12, %13, %14, %15, %16, %17, %18, %19, %20, %21, %22, %23, %24, %25, %26, %27, %28, %29, %30, %31, %32, %33, %34, %35, %36, %37, %38, %39, %40, %41, %42, %43, %44, %45, %46, %47, %48, %49, %50, %51, %52, %53, %54, %55, %56, %57, %58, %59, %60, %61, %62, %63, %64, %65, %66, %67, %68, %69, %70, %71}, %72, %73, 1, 1, 1, %75, %74;"
     : "+f"(d[0]), "+f"(d[1]), "+f"(d[2]), "+f"(d[3]), "+f"(d[4]), "+f"(d[5]), "+f"(d[6]), "+f"(d[7]), "+f"(d[8]), "+f"(d[9]), "+f"(d[10]), "+f"(d[11]), "+f"(d[12]), "+f"(d[13]), "+f"(d[14]), "+f"(d[15]), "+f"(d[16]), "+f"(d[17]), "+f"(d[18]), "+f"(d[19]), "+f"(d[20]), "+f"(d[21]), "+f"(d[22]), "+f"(d[23]), "+f"(d[24]), "+f"(d[25]), "+f"(d[26]), "+f"(d[27]), "+f"(d[28]), "+f"(d[29]), "+f"(d[30]), "+f"(d[31]), "+f"(d[32]), "+f"(d[33]), "+f"(d[34]), "+f"(d[35]), "+f"(d[36]), "+f"(d[37]), "+f"(d[38]), "+f"(d[39]), "+f"(d[40]), "+f"(d[41]), "+f"(d[42]), "+f"(d[43]), "+f"(d[44]), "+f"(d[45]), "+f"(d[46]), "+f"(d[47]), "+f"(d[48]), "+f"(d[49]), "+f"(d[50]), "+f"(d[51]), "+f"(d[52]), "+f"(d[53]), "+f"(d[54]), "+f"(d[55]), "+f"(d[56]), "+f"(d[57]), "+f"(d[58]), "+f"(d[59]), "+f"(d[60]), "+f"(d[61]), "+f"(d[62]), "+f"(d[63]), "+f"(d[64]), "+f"(d[65]), "+f"(d[66]), "+f"(d[67]), "+f"(d[68]), "+f"(d[69]), "+f"(d[70]), "+f"(d[71])
     : "l"(da), "l"(db), "n"(TB), "n"(TA));
  }
}
template<int TB, bool FIRST, int TA = 0> __device__ __forceinline__ void wgmma_n192(float (&d)[96], uint64_t da, uint64_t db){
  if (FIRST) {
    asm volatile("wgmma.mma_async.sync.aligned.m64n192k16.f32.bf16.bf16 {%0, %1, %2, %3, %4, %5, %6, %7, %8, %9, %10, %11, %12, %13, %14, %15, %16, %17, %18, %19, %20, %21, %22, %23, %24, %25, %26, %27, %28, %29, %30, %31, %32, %33, %34, %35, %36, %37, %38, %39, %40, %41, %42, %43, %44, %45, %46, %47, %48, %49, %50, %51, %52, %53, %54, %55, %56, %57, %58, %59, %60, %61, %62, %63, %64, %65, %66, %67, %68, %69, %70, %71, %72, %73, %74, %75, %76, %77, %78, %79, %80, %81, %82, %83, %84, %85, %86, %87, %88, %89, %90, %91, %92, %93, %94, %95}, %96, %97, 0, 1, 1, %99, %98;"
     : "=f"(d[0]), "=f"(d[1]), "=f"(d[2]), "=f"(d[3]), "=f"(d[4]), "=f"(d[5]), "=f"(d[6]), "=f"(d[7]), "=f"(d[8]), "=f"(d[9]), "=f"(d[10]), "=f"(d[11]), "=f"(d[12]), "=f"(d[13]), "=f"(d[14]), "=f"(d[15]), "=f"(d[16]), "=f"(d[17]), "=f"(d[18]), "=f"(d[19]), "=f"(d[20]), "=f"(d[21]), "=f"(d[22]), "=f"(d[23]), "=f"(d[24]), "=f"(d[25]), "=f"(d[26]), "=f"(d[27]), "=f"(d[28]), "=f"(d[29]), "=f"(d[30]), "=f"(d[31]), "=f"(d[32]), "=f"(d[33]), "=f"(d[34]), "=f"(d[35]), "=f"(d[36]), "=f"(d[37]), "=f"(d[38]), "=f"(d[39]), "=f"(d[40]), "=f"(d[41]), "=f"(d[42]), "=f"(d[43]), "=f"(d[44]), "=f"(d[45]), "=f"(d[46]), "=f"(d[47]), "=f"(d[48]), "=f"(d[49]), "=f"(d[50]), "=f"(d[51]), "=f"(d[52]), "=f"(d[53]), "=f"(d[54]), "=f"(d[55]), "=f"(d[56]), "=f"(d[57]), "=f"(d[58]), "=f"(d[59]), "=f"(d[60]), "=f"(d[61]), "=f"(d[62]), "=f"(d[63]), "=f"(d[64]), "=f"(d[65]), "=f"(d[66]), "=f"(d[67]), "=f"(d[68]), "=f"(d[69]), "=f"(d[70]), "=f"(d[71]), "=f"(d[72]), "=f"(d[73]), "=f"(d[74]), "=f"(d[75]), "=f"(d[76]), "=f"(d[77]), "=f"(d[78]), "=f"(d[79]), "=f"(d[80]), "=f"(d[81]), "=f"(d[82]), "=f"(d[83]), "=f"(d[84]), "=f"(d[85]), "=f"(d[86]), "=f"(d[87]), "=f"(d[88]), "=f"(d[89]), "=f"(d[90]), "=f"(d[91]), "=f"(d[92]), "=f"(d[93]), "=f"(d[94]), "=f"(d[95])
     : "l"(da), "l"(db), "n"(TB), "n"(TA));
  } else {
    asm volatile("wgmma.mma_async.sync.aligned.m64n192k16.f32.bf16.bf16 {%0, %1, %2, %3, %4, %5, %6, %7, %8, %9, %10, %11, %12, %13, %14, %15, %16, %17, %18, %19, %20, %21, %22, %23, %24, %25, %26, %27, %28, %29, %30, %31, %32, %33, %34, %35, %36, %37, %38, %39, %40, %41, %42, %43, %44, %45, %46, %47, %48, %49, %50, %51, %52, %53, %54, %55, %56, %57, %58, %59, %60, %61, %62, %63, %64, %65, %66, %67, %68, %69, %70, %71, %72, %73, %74, %75, %76, %77, %78, %79, %80, %81, %82, %83, %84, %85, %86, %87, %88, %89, %90, %91, %92, %93, %94, %95}, %96, %97, 1, 1, 1, %99, %98;"
     : "+f"(d[0]), "+f"(d[1]), "+f"(d[2]), "+f"(d[3]), "+f"(d[4]), "+f"(d[5]), "+f"(d[6]), "+f"(d[7]), "+f"(d[8]), "+f"(d[9]), "+f"(d[10]), "+f"(d[11]), "+f"(d[12]), "+f"(d[13]), "+f"(d[14]), "+f"(d[15]), "+f"(d[16]), "+f"(d[17]), "+f"(d[18]), "+f"(d[19]), "+f"(d[20]), "+f"(d[21]), "+f"(d[22]), "+f"(d[23]), "+f"(d[24]), "+f"(d[25]), "+f"(d[26]), "+f"(d[27]), "+f"(d[28]), "+f"(d[29]), "+f"(d[30]), "+f"(d[31]), "+f"(d[32]), "+f"(d[33]), "+f"(d[34]), "+f"(d[35]), "+f"(d[36]), "+f"(d[37]), "+f"(d[38]), "+f"(d[39]), "+f"(d[40]), "+f"(d[41]), "+f"(d[42]), "+f"(d[43]), "+f"(d[44]), "+f"(d[45]), "+f"(d[46]), "+f"(d[47]), "+f"(d[48]), "+f"(d[49]), "+f"(d[50]), "+f"(d[51]), "+f"(d[52]), "+f"(d[53]), "+f"(d[54]), "+f"(d[55]), "+f"(d[56]), "+f"(d[57]), "+f"(d[58]), "+f"(d[59]), "+f"(d[60]), "+f"(d[61]), "+f"(d[62]), "+f"(d[63]), "+f"(d[64]), "+f"(d[65]), "+f"(d[66]), "+f"(d[67]), "+f"(d[68]), "+f"(d[69]), "+f"(d[70]), "+f"(d[71]), "+f"(d[72]), "+f"(d[73]), "+f"(d[74]), "+f"(d[75]), "+f"(d[76]), "+f"(d[77]), "+f"(d[78]), "+f"(d[79]), "+f"(d[80]), "+f"(d[81]), "+f"(d[82]), "+f"(d[83]), "+f"(d[84]), "+f"(d[85]), "+f"(d[86]), "+f"(d[87]), "+f"(d[88]), "+f"(d[89]), "+f"(d[90]), "+f"(d[91]), "+f"(d[92]), "+f"(d[93]), "+f"(d[94]), "+f"(d[95])
     : "l"(da), "l"(db), "n"(TB), "n"(TA));
  }
}

__device__ __forceinline__ uint32_t clock32() { uint32_t t; asm volatile("mov.u32 %0, %%clock;" : "=r"(t)); return t; }
__device__ __forceinline__ bool elect_one() {
  uint32_t pred;
  asm volatile("{\n.reg .pred p;\nelect.sync _|p, 0xffffffff;\nselp.u32 %0, 1, 0, p;\n}" : "=r"(pred));
  return pred != 0;
}
__device__ __forceinline__ void mbar_init(uint32_t b, int c) { asm volatile("mbarrier.init.shared::cta.b64 [%0], %1;" ::"r"(b), "r"(c) : "memory"); }
__device__ __forceinline__ void mbar_expect(uint32_t b, int bytes) { asm volatile("mbarrier.arrive.expect_tx.shared::cta.b64 _, [%0], %1;" ::"r"(b), "r"(bytes) : "memory"); }
__device__ __forceinline__ void mbar_arrive(uint32_t b) { asm volatile("mbarrier.arrive.shared::cta.b64 _, [%0];" ::"r"(b) : "memory"); }
__device__ __forceinline__ void mbar_arrive_if(uint32_t b, uint32_t pred) {
  asm volatile("{\n.reg .pred p;\nsetp.ne.u32 p, %1, 0;\n@p mbarrier.arrive.shared::cta.b64 _, [%0];\n}" ::"r"(b), "r"(pred) : "memory");
}
#define WAIT_LIMIT "2000000"
#define DIE_ADDR "l"(0ull)
#define DIE_ST "st.global.u32 [%2], %1;\n"
__device__ __forceinline__ void mbar_wait(uint32_t b, uint32_t ph) {
  asm volatile(
      "{\n.reg .pred p;\n.reg .u32 c;\nmov.u32 c, 0;\n"
      "W:\nmbarrier.try_wait.parity.shared::cta.b64 p, [%0], %1, 1000;\n@p bra D;\n"
      "add.u32 c, c, 1;\nsetp.lt.u32 p, c, " WAIT_LIMIT ";\n@p bra W;\n" DIE_ST
      "D:\n}" ::"r"(b), "r"(ph), DIE_ADDR : "memory");
}
__device__ __forceinline__ uint32_t mbar_test(uint32_t b, uint32_t ph) {
  uint32_t ok;
  asm volatile("{\n.reg .pred p;\nmbarrier.test_wait.parity.shared::cta.b64 p, [%1], %2;\nselp.u32 %0, 1, 0, p;\n}" : "=r"(ok) : "r"(b), "r"(ph) : "memory");
  return ok;
}
__device__ __forceinline__ void cnt_arrive(int idx) {
  asm volatile("red.release.gpu.global.add.u32 [%0], 1;" ::"l"(&g_cnt[idx * CNT_STRIDE]) : "memory");
}
__device__ __forceinline__ void cnt_wait(uint32_t idx, uint32_t target) {
  asm volatile(
      "{\n.reg .pred p;\n.reg .u32 c, v;\nmov.u32 c, 0;\n"
      "W:\nld.acquire.gpu.global.u32 v, [%3];\nsub.u32 v, v, %1;\nsetp.ge.s32 p, v, 0;\n@p bra D;\n"
      "add.u32 c, c, 1;\nsetp.lt.u32 p, c, " WAIT_LIMIT ";\n@p bra W;\n" DIE_ST
      "D:\n}" ::"r"(idx | 0x80000000u), "r"(target), DIE_ADDR, "l"(&g_cnt[idx * CNT_STRIDE]) : "memory");
}
__device__ __forceinline__ void release_x(uint32_t fdone, uint32_t ph, int cnt, int n, uint32_t mask, int ev) {
#pragma unroll 1
  for (int k = 0; k < n;) {
    int e = k + __ffs(mask >> k);
    mbar_wait(fdone + 8 * (e - 1), ph);
    if (ev) for (int j = k; j < e; j++) EV(32 + j);
    asm volatile("fence.release.gpu;" ::: "memory");
    asm volatile("red.relaxed.gpu.global.add.u32 [%0], 1;" ::"l"(&g_cnt[(cnt + e - 1) * CNT_STRIDE]) : "memory");
    if (ev) for (int j = k; j < e; j++) EV(48 + j);
    k = e;
  }
}
__device__ __forceinline__ uint4 lds128(uint32_t a) {
  uint4 v;
  asm volatile("ld.shared.v4.u32 {%0,%1,%2,%3}, [%4];" : "=r"(v.x), "=r"(v.y), "=r"(v.z), "=r"(v.w) : "r"(a) : "memory");
  return v;
}
__device__ __forceinline__ void stat_publish(ulonglong2* p, float s, float qq, uint32_t ep1) {
  const float mean = s * (1.0f / DM);
  const float rstd = rsqrtf(fmaxf(qq * (1.0f / DM) - mean * mean, 0.f) + 1e-5f);
  const unsigned long long tag = (unsigned long long)ep1 << 32;
  asm volatile("st.relaxed.gpu.global.v2.u64 [%0], {%1, %2};" ::"l"(p), "l"(tag | __float_as_uint(rstd)), "l"(tag | __float_as_uint(-mean)) : "memory");
}
__device__ __forceinline__ void stat_gather(const ulonglong2* p, uint32_t tag, float* rsd, float* md) {
  unsigned long long a[4], b[4];
#pragma unroll 1
  for (uint32_t it = 0;; it++) {
    bool ok = true;
#pragma unroll
    for (int i = 0; i < 4; i++) asm volatile("ld.relaxed.gpu.global.v2.u64 {%0, %1}, [%2];" : "=l"(a[i]), "=l"(b[i]) : "l"(p + i * 32) : "memory");
#pragma unroll
    for (int i = 0; i < 4; i++) ok = ok && (uint32_t)(a[i] >> 32) == tag && (uint32_t)(b[i] >> 32) == tag;
    if (ok) break;
    if (it > 2000000u) { asm volatile("st.global.u32 [%0], %1;" ::"l"(0ull), "r"(0) : "memory"); break; }
  }
#pragma unroll
  for (int i = 0; i < 4; i++) {
    rsd[i * 32] = __uint_as_float((uint32_t)a[i]);
    if (md) md[i * 32] = __uint_as_float((uint32_t)b[i]);
  }
}
__device__ __forceinline__ void pace(uint32_t t0, uint32_t dt) { while (clock32() - t0 < dt) __nanosleep(20); }
__device__ __forceinline__ void spin_until(uint32_t t) {
  asm volatile("{\n.reg .pred p;\n.reg .u32 c;\nW:\nmov.u32 c, %%clock;\nsub.u32 c, c, %0;\nsetp.lt.s32 p, c, 0;\n@p nanosleep.u32 40;\n@p bra W;\n}" ::"r"(t) : "memory");
}
__device__ __forceinline__ void tma2d(uint32_t dst, const CUtensorMap* m, uint32_t bar, int c0, int c1) {
  asm volatile("cp.async.bulk.tensor.2d.shared::cluster.global.mbarrier::complete_tx::bytes [%0], [%1, {%3, %4}], [%2];" ::"r"(dst), "l"(m), "r"(bar), "r"(c0), "r"(c1) : "memory");
}
__device__ __forceinline__ void tma2d_ef(uint32_t dst, const CUtensorMap* m, uint32_t bar, int c0, int c1) {
  asm volatile("{\n.reg .b64 pol;\ncreatepolicy.fractional.L2::evict_first.b64 pol, 1.0;\n"
               "cp.async.bulk.tensor.2d.shared::cluster.global.mbarrier::complete_tx::bytes.L2::cache_hint [%0], [%1, {%3, %4}], [%2], pol;\n}"
               ::"r"(dst), "l"(m), "r"(bar), "r"(c0), "r"(c1) : "memory");
}
__device__ __forceinline__ void tma3d(uint32_t dst, const CUtensorMap* m, uint32_t bar, int c0, int c1, int c2) {
  asm volatile("cp.async.bulk.tensor.3d.shared::cluster.global.mbarrier::complete_tx::bytes [%0], [%1, {%3, %4, %5}], [%2];" ::"r"(dst), "l"(m), "r"(bar), "r"(c0), "r"(c1), "r"(c2) : "memory");
}
__device__ __forceinline__ void tma3d_mc(uint32_t dst, const CUtensorMap* m, uint32_t bar, int c0, int c1, int c2) {
  asm volatile("cp.async.bulk.tensor.3d.shared::cluster.global.mbarrier::complete_tx::bytes.multicast::cluster [%0], [%1, {%3, %4, %5}], [%2], %6;"
               ::"r"(dst), "l"(m), "r"(bar), "r"(c0), "r"(c1), "r"(c2), "h"((uint16_t)3) : "memory");
}
__device__ __forceinline__ uint32_t map_rank(uint32_t a, uint32_t rank) {
  uint32_t v;
  asm("mapa.shared::cluster.u32 %0, %1, %2;" : "=r"(v) : "r"(a), "r"(rank));
  return v;
}
__device__ __forceinline__ void mbar_arrive_cl_if(uint32_t b, uint32_t pred) {
  asm volatile("{\n.reg .pred p;\nsetp.ne.u32 p, %1, 0;\n@p mbarrier.arrive.shared::cluster.b64 _, [%0];\n}" ::"r"(b), "r"(pred) : "memory");
}
__device__ __forceinline__ void bulk_pf(const void* p, int bytes) {
  asm volatile("cp.async.bulk.prefetch.L2.global [%0], %1;" ::"l"(p), "r"(bytes) : "memory");
}
__device__ __forceinline__ void tma_st2d(const CUtensorMap* m, uint32_t src, int c0, int c1) {
  asm volatile("cp.async.bulk.tensor.2d.global.shared::cta.tile.bulk_group [%0, {%2, %3}], [%1];" ::"l"(m), "r"(src), "r"(c0), "r"(c1) : "memory");
}
__device__ __forceinline__ void tma_red2d(const CUtensorMap* m, uint32_t src, int c0, int c1) {
  asm volatile("cp.reduce.async.bulk.tensor.2d.global.shared::cta.add.tile.bulk_group [%0, {%2, %3}], [%1];" ::"l"(m), "r"(src), "r"(c0), "r"(c1) : "memory");
}
__device__ __forceinline__ void bulk_commit() { asm volatile("cp.async.bulk.commit_group;" ::: "memory"); }
__device__ __forceinline__ void bulk_wait0() { asm volatile("cp.async.bulk.wait_group 0;" ::: "memory"); }
__device__ __forceinline__ void fence_async_smem() { asm volatile("fence.proxy.async.shared::cta;" ::: "memory"); }
__device__ __forceinline__ void fence_async_all() { asm volatile("fence.proxy.async.global;" ::: "memory"); }
__device__ __forceinline__ void wg_fence() { asm volatile("wgmma.fence.sync.aligned;" ::: "memory"); }
__device__ __forceinline__ void wg_commit() { asm volatile("wgmma.commit_group.sync.aligned;" ::: "memory"); }
template <int N> __device__ __forceinline__ void wg_wait() { asm volatile("wgmma.wait_group.sync.aligned %0;" ::"n"(N) : "memory"); }
__device__ __forceinline__ uint32_t pk(float a, float b) {
  uint32_t r;
  asm("cvt.rn.bf16x2.f32 %0, %1, %2;" : "=r"(r) : "f"(b), "f"(a));
  return r;
}
__device__ __forceinline__ uint32_t pk_relu(float a, float b) {
  uint32_t r;
  asm("cvt.rn.relu.bf16x2.f32 %0, %1, %2;" : "=r"(r) : "f"(b), "f"(a));
  return r;
}
__device__ __forceinline__ float bf_lo(uint32_t v) { return __uint_as_float(v << 16); }
__device__ __forceinline__ float bf_hi(uint32_t v) { return __uint_as_float(v & 0xffff0000u); }
__device__ __forceinline__ void stsm4(uint32_t addr, uint32_t a0, uint32_t a1, uint32_t a2, uint32_t a3) {
  asm volatile("stmatrix.sync.aligned.m8n8.x4.shared.b16 [%0], {%1,%2,%3,%4};" ::"r"(addr), "r"(a0), "r"(a1), "r"(a2), "r"(a3));
}
__device__ __forceinline__ float lds32f(uint32_t a) {
  float v;
  asm volatile("ld.shared.f32 %0, [%1];" : "=f"(v) : "r"(a) : "memory");
  return v;
}
__device__ __forceinline__ float2 lds64f(uint32_t a) {
  float2 v;
  asm volatile("ld.shared.v2.f32 {%0,%1}, [%2];" : "=f"(v.x), "=f"(v.y) : "r"(a) : "memory");
  return v;
}
template <int R> __device__ __forceinline__ void reg_fence(float (&d)[R]) {
#pragma unroll
  for (int i = 0; i < R; i++) asm volatile("" : "+f"(d[i])::"memory");
}
constexpr uint32_t DESC_HI_128 = (1024u >> 4) | (1u << 30);
__device__ __forceinline__ uint64_t desc(uint32_t lo, uint32_t hi) {
  uint64_t d;
  asm("mov.b64 %0, {%1, %2};" : "=l"(d) : "r"(lo), "r"(hi));
  return d;
}

__device__ __forceinline__ void sum8(uint4 v, float& s, float& q) {
  float a;
  a = bf_lo(v.x); s += a; q = fmaf(a, a, q);  a = bf_hi(v.x); s += a; q = fmaf(a, a, q);
  a = bf_lo(v.y); s += a; q = fmaf(a, a, q);  a = bf_hi(v.y); s += a; q = fmaf(a, a, q);
  a = bf_lo(v.z); s += a; q = fmaf(a, a, q);  a = bf_hi(v.z); s += a; q = fmaf(a, a, q);
  a = bf_lo(v.w); s += a; q = fmaf(a, a, q);  a = bf_hi(v.w); s += a; q = fmaf(a, a, q);
}

#define G3A_C1 8
#define G3B_C1 6
#define G3A_C2 12
#define G3B_C2 10
#define MAPMODE 0
#define CLUSTER 2
#define CPF_DT 520
#define CPF_LAG 3
#define CPF_START -1
#define CLD_DT 900
#define FLUSH_DT 860
#define FLUSH_DT_LAST 0
#define STAGGER 1
#define FRONT 0
#define EVPH 2
#define FLUSH_DT_D 450
#define CPF2_DT 400
#define HPF_D_START 78000
#define HW1_START 10000
#define HPF_C_START 50000
#define XEARLY2 3
#define XEARLY4 6
#define FLUSH_DT4 870
#define RELMASK2 0x1AC
#define RELMASK4 0x12A
#define FLUSH_DT_A 840
#define XFIRST 5
#define AG_DT 200
#define GO_EARLY 1
#define CL0_T0 1000
#define REST_AFTER 0
#define REST_T0 700
#define CE1 6
#define CE1_DT 1300
#define CL0_DT 1250
#define CL0_DT2 1000
#define CL0_N 6
#define CE1_AFTER 2
#define CPROMO CU_TENSOR_MAP_L2_PROMOTION_L2_128B
#define XPROMO CU_TENSOR_MAP_L2_PROMOTION_L2_128B
#define XG 9
#define DG 3
#define DGD 0
#define CE1_BAR BAR_REL8
#define CE1_PH 0
#define XFIRST0 1
#define X2_DT 700
#define X2_DT2 300
#define FLUSH_DT_E 750
#define CEARLY 2
#define XLD_DT 0
#define XLD_T0 0

__global__ void __launch_bounds__(384, 1)
fnet_ffn_kernel(const __grid_constant__ Maps maps, const __nv_bfloat16* __restrict__ xin, const __nv_bfloat16* __restrict__ cre,
                const __nv_bfloat16* __restrict__ cim, const __nv_bfloat16* __restrict__ dre,
                const __nv_bfloat16* __restrict__ dim, const __nv_bfloat16* __restrict__ w1, const __nv_bfloat16* __restrict__ w2,
                __nv_bfloat16* xout) {
  extern __shared__ __align__(1024) unsigned char smem[];
  const uint32_t sb = __shfl_sync(0xffffffffu, (uint32_t)__cvta_generic_to_shared(smem), 0);
  constexpr uint32_t sbd = 1024;
  const int tid = threadIdx.x;
  const int wg = __shfl_sync(0xffffffffu, tid >> 7, 0);
  const int warp = __shfl_sync(0xffffffffu, (tid >> 5) & 3, 0);
  const int lane = tid & 31;
  if (tid == 0) EV(110);
  if (blockIdx.x < NHELP) {
    if (tid == 0) atomicAdd(&g_cnt[CNT_TICKET * CNT_STRIDE], 1u);
    const uint32_t th0 = clock32();
    constexpr int HS = 16, HG = DFF / 192 / NHELP;
    const uint32_t hb = sb + HS * B_SLOT + 8192;
    if (tid == 0) {
#pragma unroll
      for (int i = 0; i < 2 * HS; i++) mbar_init(hb + 8 * i, 1);
      asm volatile("fence.mbarrier_init.release.cluster;" ::: "memory");
    }
    for (int i = tid; i < 2048; i += 384) reinterpret_cast<uint32_t*>(smem + HS * B_SLOT)[i] = 0x3f803f80u;
    fence_async_smem();
    __syncthreads();
    if (wg == 0) {
      int slot = 0, ph = 0;
#pragma unroll 1
      for (int g = 0; g < HG; g++) {
        float acc[96];
#pragma unroll
        for (int i = 0; i < 96; i++) acc[i] = 0.f;
#pragma unroll 1
        for (int st = 0; st < 18; st++) {
          mbar_wait(hb + 8 * slot, ph);
          const uint32_t blo = (((sbd + slot * B_SLOT) >> 4) | ((4096u >> 4) << 16));
          const uint64_t da = desc(((sbd + HS * B_SLOT) >> 4) | (1u << 16), DESC_HI_128);
          wg_fence();
          wgmma_n192<1, false>(acc, da, desc(blo, DESC_HI_128));
          wgmma_n192<1, false>(acc, da, desc(blo + 128, DESC_HI_128));
          wg_commit();
          wg_wait<1>();
          mbar_arrive_if(hb + 8 * (HS + ((slot + HS - 1) & (HS - 1))), tid == 0 && (g | st));
          if (++slot == HS) { slot = 0; ph ^= 1; }
        }
        wg_wait<0>();
        reg_fence(acc);
        if (tid < 4) {
#pragma unroll
          for (int b = 0; b < 24; b++)
            *reinterpret_cast<float2*>(g_cs1 + (blockIdx.x * HG + g) * 192 + b * 8 + tid * 2) = make_float2(acc[b * 4], acc[b * 4 + 1]);
        }
      }
      __syncwarp();
      if (tid == 0) { cnt_arrive(CNT_CS); EV(100); }
    } else if (tid == 128) {
      int slot = 0, ph = 1;
      pace(th0, HW1_START);
#pragma unroll 1
      for (int i = 0; i < HG * 18; i++) {
        mbar_wait(hb + 8 * (HS + slot), ph);
        mbar_expect(hb + 8 * slot, B_SLOT);
        tma3d(sb + slot * B_SLOT, &maps.w1, hb + 8 * slot, 0, (i % 18) * 32, (blockIdx.x * HG + i / 18) * 3);
        if (++slot == HS) { slot = 0; ph ^= 1; }
      }
      constexpr int W2N = DM * DFF * 2 / NHELP / 8192;
#pragma unroll 1
      for (int i = 0; i < W2N; i++) bulk_pf(reinterpret_cast<const char*>(w2) + (size_t)(blockIdx.x * W2N + i) * 8192, 8192);
      EV(101);
      pace(th0, HPF_D_START);
#pragma unroll 1
      for (int i = 0; i < 81; i++) bulk_pf(reinterpret_cast<const char*>((blockIdx.x & 1) ? dim : dre) + ((blockIdx.x >> 1) * 81 + i) * 4096, 4096);
      EV(102);
    }
    return;
  }
  const int cta = blockIdx.x - NHELP;
  const int r = cta & 15, p = cta >> 4;
  const int m = p >> 2, q = p & 3;
  const int rank = cta & 1;
  const uint32_t bar0 = sb + OFF_BAR;
#define BAR(i) (bar0 + 8u * (uint32_t)(i))
#define START_SYNC() do { __syncwarp(); asm volatile("barrier.cluster.wait.acquire.aligned;" ::: "memory"); } while (0)

  uint32_t ticket = 0;
  if (elect_one()) {
    const int w12 = wg * 4 + warp;
#pragma unroll
    for (int i = 0; i < 16; i++) mbar_init(BAR(w12 * 16 + i), w12 < 2 ? 4 : (w12 == 2 ? 2 : 1));
    asm volatile("fence.mbarrier_init.release.cluster;" ::: "memory");
    if (w12 == 8) {
      fence_async_smem();
#pragma unroll 1
      for (int k = 0; k < XFIRST0; k++) {
        mbar_expect(BAR(BAR_XF + k), A_SLOT);
        tma2d(sb + OFF_A + k * A_SLOT, &maps.xin, BAR(BAR_XF + k), k * 64, r * 128);
      }
    }
  }
  __syncwarp();
  asm volatile("barrier.cluster.arrive.relaxed.aligned;" ::: "memory");
  if (wg == 2 && warp == 0) {
    START_SYNC();
    if (elect_one()) {
#pragma unroll 1
      for (int k = 0; k < 4; k++) {
        mbar_expect(BAR(BAR_DF + k), D_SLOT);
        if ((k & 1) == rank) tma3d_mc(sb + OFF_B + k * D_SLOT, m ? &maps.di : &maps.dr, BAR(BAR_DF + k), k * 64, q * 48, 0);
        if (k + XFIRST0 < XFIRST) {
          mbar_expect(BAR(BAR_XF + k + XFIRST0), A_SLOT);
          tma2d(sb + OFF_A + (k + XFIRST0) * A_SLOT, &maps.xin, BAR(BAR_XF + k + XFIRST0), (k + XFIRST0) * 64, r * 128);
        }
      }
    }
    __syncwarp();
  }
  if (tid == 320) asm volatile("atom.relaxed.gpu.global.add.u32 %0, [%1], 1;" : "=r"(ticket) : "l"(&g_cnt[CNT_TICKET * CNT_STRIDE]));

  if (wg == 2) {
    asm volatile("setmaxnreg.dec.sync.aligned.u32 40;");
    if (warp & 1) START_SYNC();
    if (warp == 0) {
      const CUtensorMap* mD = m ? &maps.di : &maps.dr;
      if (elect_one()) {
        EV(113);
        int slot = 0, ph = 1;
#pragma unroll 1
        for (int layer = 0; layer < 2; layer++) {
#pragma unroll 1
          for (int s = 0; s < 9; s++) {
            if (s < 3) {
              const int nacq = layer ? (s == 0 ? 3 : 1) : 2;
#pragma unroll 1
              for (int i = 0; i < nacq; i++) {
                mbar_wait(BAR(BAR_BEMPTY + slot), ph);
                mbar_arrive(BAR(BAR_BFULL + slot));
                if (++slot == NB + 1 - layer) { slot = 0; ph ^= 1; }
              }
            } else if (s == 3) {
              if (layer) {
                mbar_wait(BAR(BAR_FDONE + 16), 0);
                mbar_arrive_cl_if(map_rank(BAR(BAR_STGF), 0), 1);
                mbar_arrive_cl_if(map_rank(BAR(BAR_STGF), 1), 1);
                mbar_wait(BAR(BAR_STGF), 0);
              }
            } else {
              mbar_wait(BAR(BAR_DREL + s - 4), layer);
            }
            if (layer && s == DG) mbar_wait(BAR(BAR_REL8), 0);
            if (layer || s >= 4) {
              mbar_expect(BAR(BAR_DF + s), D_SLOT);
              if ((s & 1) == rank) tma3d_mc(sb + OFF_B + (s & 3) * D_SLOT, mD, BAR(BAR_DF + s), s * 64, q * 48, 0);
              const int k = s - 4 + XFIRST;
              if (layer == 0 && k < 9) {
                mbar_expect(BAR(BAR_XF + k), A_SLOT);
                tma2d(sb + OFF_A + k * A_SLOT, &maps.xin, BAR(BAR_XF + k), k * 64, r * 128);
              }
            }
          }
          if (layer) {
            mbar_wait(BAR(BAR_BEMPTY + slot), ph);
            mbar_arrive(BAR(BAR_BFULL + slot));
            mbar_arrive(BAR(BAR_BEMPTY + slot));
            mbar_arrive(BAR(BAR_BEMPTY + slot));
            slot = 0; ph ^= 1;
          }
#pragma unroll 1
          for (int sg = -2; sg < 18; sg++) {
            const CUtensorMap* mm;
            int row, atom, cw, n, dk = 32;
            if (sg < 4) {
              mm = &maps.abld; row = (layer * 2 + m) * SEQ + q * 512;
              if (sg < 2) { mbar_wait(BAR(BAR_ABOK + sg + 2), layer); row += (sg + 2) * 128; atom = 0; cw = 1; n = 4; if (sg == -2) EV(6 + layer * 16); }
              else { mbar_wait(BAR(sg == 2 ? BAR_AB1 : BAR_FOK), layer); atom = (sg - 1) * 3; cw = sg & 1; n = 16; }
            } else if (sg < 13) {
              mm = &maps.w1;
              if (sg < 10) {
                cw = sg & 1;
                const int c1 = cw ? G3B_C1 : G3A_C1, c2 = cw ? G3B_C2 : G3A_C2;
                const int lo = sg < 6 ? 0 : (sg < 8 ? c1 : c2), hi = sg < 6 ? c1 : (sg < 8 ? c2 : 18);
                atom = p * 9 + cw * 3; row = lo * 32; n = hi - lo;
              } else { cw = 0; atom = p * 9 + 6; row = (12 - sg) * 192; n = 6; }
            } else {
              row = p * 576; cw = sg & 1;
              atom = (sg - 13) * 2;
              if (sg < 17) { mm = &maps.w2; n = 12; dk = 48; }
              else { mm = &maps.w2n; n = 6; dk = 96; }
            }
            const uint32_t fb0 = BAR(BAR_BFULL);
            const int nsl = sg < 13 ? NB + 1 : NB;
            if (sg == -1) mbar_wait(BAR(BAR_STG2), layer);
#pragma unroll 1
            for (int i = 0; i < n; i++) {
              mbar_wait(BAR(BAR_BEMPTY + slot), ph);
              mbar_expect(fb0 + 8 * slot, B_SLOT);
              if ((i & 1) == rank) tma3d_mc(sb + OFF_B + slot * B_SLOT, mm, fb0 + 8 * slot, 0, row, atom);
              row += dk;
              if (++slot == nsl) { slot = 0; ph ^= 1; }
            }
          }
        }
#pragma unroll 1
        for (int i = 0; i < NB; i++) {
          mbar_wait(BAR(BAR_BEMPTY + slot), ph);
          if (++slot == NB) { slot = 0; ph ^= 1; }
        }
      }
    } else if (warp == 1) {
      if (lane == 0) {
        asm volatile("prefetch.tensormap [%0];" ::"l"(m ? &maps.ci : &maps.cr) : "memory");
        asm volatile("prefetch.tensormap [%0];" ::"l"(&maps.abst) : "memory");
        asm volatile("prefetch.tensormap [%0];" ::"l"(&maps.abld) : "memory");
      }
      mbar_wait(BAR(BAR_EPOCH), 0);
      const uint32_t ep1 = *reinterpret_cast<volatile uint32_t*>(smem + OFF_EPOCH);
      {
        unsigned long long a[3], b[3];
#pragma unroll 1
        for (uint32_t it = 0;; it++) {
          bool ok = true;
#pragma unroll
          for (int i = 0; i < 3; i++)
            asm volatile("ld.relaxed.gpu.global.v2.u64 {%0, %1}, [%2];" : "=l"(a[i]), "=l"(b[i]) : "l"(&g_csd[p * 144 + min(lane + i * 32, 71) * 2]) : "memory");
#pragma unroll
          for (int i = 0; i < 3; i++) ok = ok && (uint32_t)(a[i] >> 32) == ep1 && (uint32_t)(b[i] >> 32) == ep1;
          if (ok) break;
          if (it > 2000000u) { asm volatile("st.global.u32 [%0], %1;" ::"l"(0ull), "r"(0) : "memory"); break; }
        }
#pragma unroll
        for (int i = 0; i < 3; i++)
          reinterpret_cast<float2*>(smem + OFF_CSD)[min(lane + i * 32, 71)] = make_float2(__uint_as_float((uint32_t)a[i]), __uint_as_float((uint32_t)b[i]));
        __syncwarp();
        mbar_arrive_if(BAR(BAR_CSD), lane == 0);
        if (lane == 0) EV(10);
      }
      if (lane == 0) {
#pragma unroll 1
        for (int layer = 0; layer < 2; layer++) {
          const int abrow = (layer * 2 + m) * SEQ + r * 128;
          const int abcnt = CNT_AB + ((layer * 2 + m) * 16 + r) * 3;
          mbar_wait(BAR(BAR_ABSTG), layer);
          EV(3 + layer * 16);
          tma_st2d(&maps.abst, sb + OFF_STG, q * 48, abrow);
          bulk_commit();
          bulk_wait0();
          EV(4 + layer * 16);
          cnt_arrive(abcnt);
          mbar_arrive_cl_if(map_rank(BAR(BAR_STG2), 0), 1);
          mbar_arrive_cl_if(map_rank(BAR(BAR_STG2), 1), 1);
          EV(5 + layer * 16);
          mbar_wait(BAR(BAR_ABSTG + 1), layer);
          mbar_wait(BAR(BAR_ABOK + REST_AFTER), layer);
          spin_until(clock32() + REST_T0);
          tma_st2d(&maps.abst, sb + OFF_A + 7 * A_SLOT, 192 + q * 48, abrow);
          bulk_commit();
          bulk_wait0();
          mbar_arrive(BAR(BAR_A7));
          cnt_arrive(abcnt + 1);
          tma_st2d(&maps.abst, sb + OFF_A + 8 * A_SLOT, 384 + q * 48, abrow);
          bulk_commit();
          bulk_wait0();
          mbar_arrive(BAR(BAR_A8));
          cnt_arrive(abcnt + 2);
          release_x(BAR(BAR_FDONE), layer, CNT_X + (layer * 2 * 16 + r) * 9, 6, RELMASK2, EVPH == layer * 2);
          {
            uint32_t tn = 0;
#pragma unroll 1
            for (int i = 0; i < 8; i++) {
              if ((i & 3) == 0) mbar_wait(BAR(BAR_FDONE + 7 + (i >> 2)), layer);
              if (i == 0) tn = clock32();
              spin_until(tn);
              tma_red2d(&maps.xred, sb + OFF_A + 7 * A_SLOT + i * 4096, 448 + (i >> 2) * 64, r * 128 + (i & 3) * 32);
              tma_red2d(&maps.xred, sb + OFF_A + 7 * A_SLOT + i * 4096 + 2048, 448 + (i >> 2) * 64, r * 128 + (i & 3) * 32 + 16);
              tn += AG_DT;
              if (i == 3) {
                bulk_commit();
                mbar_wait(BAR(BAR_FDONE + 6), layer);
                bulk_wait0();
                mbar_arrive(BAR(BAR_SENT));
              }
            }
            bulk_commit();
            bulk_wait0();
            if (EVPH == layer * 2) EV(40);
            cnt_arrive(CNT_X + (layer * 2 * 16 + r) * 9 + 8);
            if (EVPH == layer * 2) EV(56);
          }
          mbar_wait(BAR(BAR_XRD), layer);
#pragma unroll 1
          for (int s = 0; s < 3; s++) {
            mbar_wait(BAR(BAR_RG3C + s), layer);
            mbar_wait(BAR(BAR_RG3B + 6 + s), layer);
            mbar_expect(BAR(BAR_X1F + 9 + s), A_SLOT);
            tma2d(sb + OFF_A + (6 + s) * A_SLOT, &maps.xld, BAR(BAR_X1F + 9 + s), s * 64, r * 128);
          }
#pragma unroll 1
          for (int s = 0; s < 3; s++) mbar_wait(BAR(BAR_X1F + 9 + s), layer);
          cnt_arrive(CNT_G3 + layer * 16 + r);
          cnt_wait(CNT_G3 + layer * 16 + r, ep1 * 8);
          mbar_arrive(BAR(BAR_FOK + 1));
          if (layer == 0) release_x(BAR(BAR_FDONE + 9), 0, CNT_X + (16 + r) * 9, 6, RELMASK4, EVPH == 1);
          mbar_wait(BAR(BAR_FDONE + 17), layer);
          tma_red2d(&maps.xld, sb + OFF_A + 8 * A_SLOT, 512, r * 128);
          bulk_commit();
          bulk_wait0();
          if (layer == 0) {
            mbar_wait(BAR(BAR_FDONE + 16), 0);
            if (EVPH == 1) EV(40);
            asm volatile("fence.release.gpu;" ::: "memory");
            asm volatile("red.relaxed.gpu.global.add.u32 [%0], 1;" ::"l"(&g_cnt[(CNT_X + (16 + r) * 9 + 8) * CNT_STRIDE]) : "memory");
            mbar_arrive(BAR(BAR_REL8));
            if (EVPH == 1) EV(56);
          }
        }
      }
    } else if (warp == 2) {
      START_SYNC();
      if ((sb & 0x3FFFFu) != sbd) asm volatile("st.global.u32 [%0], %1;" ::"l"(0ull), "r"(0) : "memory");
      const uint32_t ep1 = __shfl_sync(0xffffffffu, ticket, 0) / NGRID + 1;
      if (lane == 0) {
        *reinterpret_cast<volatile uint32_t*>(smem + OFF_EPOCH) = ep1;
        mbar_arrive(BAR(BAR_EPOCH));
      }
      {
        stat_gather(&g_stat[r * 128 + lane], ep1, reinterpret_cast<float*>(smem + OFF_RS) + lane, reinterpret_cast<float*>(smem + OFF_MEAN) + lane);
        __syncwarp();
        mbar_arrive_if(BAR(BAR_STAT), lane == 0);
        if (lane == 0) EV(11);
      }
#pragma unroll 1
      for (int ph4 = 0; ph4 < 4; ph4++) {
        const int layer = ph4 >> 1, second = ph4 & 1;
        if (ph4) {
          const int pl = (ph4 - 1) >> 1, k = min(lane, 8);
          const uint32_t fd = BAR(BAR_FDONE + (second ? 0 : 9));
          const uint32_t fr = BAR(second ? (k < 8 ? BAR_RG2 + k : BAR_RG1 + 8) : BAR_RG4 + k);
          const uint32_t fb = BAR((second ? BAR_X1F : BAR_XF) + k);
          const int kr = k - 1 + __ffs((second ? RELMASK2 : RELMASK4) >> k);
          const uint32_t* flag = &g_cnt[(CNT_X + ((ph4 - 1) * 16 + r) * 9 + kr) * CNT_STRIDE];
          uint32_t state = lane >= 9 ? 2 : 0;
          bool needm = second;
          uint32_t tgo = 0;
          if (second) mbar_wait(BAR(BAR_STAT), layer);
          mbar_wait(fd, pl);
#pragma unroll 1
          for (uint32_t it = 0;; it++) {
            bool polled = false;
            if (state == 0 && mbar_test(fd + 8 * kr, pl)) {
              uint32_t c;
              asm volatile("ld.acquire.gpu.global.u32 %0, [%1];" : "=r"(c) : "l"(flag) : "memory");
              polled = true;
              if ((int32_t)(c - ep1 * 8) >= 0) {
                fence_async_all();
                state = 1;
                tgo = clock32() + (second ? (k < 3 ? k * X2_DT : (kr - k < 2 && k < 8 && k > 3 ? (1 - (kr - k)) * X2_DT2 : 0)) : 0);
                if (!second && k < XEARLY4) { mbar_arrive(BAR(BAR_XOK + k)); state = 2; }
                if (ph4 - 1 == EVPH) EV(64 + lane);
              }
            }
            if (state == 1 && (int32_t)(clock32() - tgo) >= 0 && mbar_test(fr, pl)) {
              mbar_expect(fb, A_SLOT);
              tma2d(sb + OFF_A + k * A_SLOT, &maps.xld, fb, k * 64, r * 128);
              state = 2;
              if (ph4 - 1 == EVPH) EV(80 + lane);
            }
            if (needm && (__ballot_sync(0xffffffffu, state != 0) & 0xff) == 0xff) {
              __syncwarp();
              float4 t;
              asm volatile("ld.relaxed.gpu.global.v4.f32 {%0,%1,%2,%3}, [%4];" : "=f"(t.x), "=f"(t.y), "=f"(t.z), "=f"(t.w) : "l"(&g_rsum[layer * SEQ + r * 128 + lane * 4]) : "memory");
              float4* mp = reinterpret_cast<float4*>(smem + OFF_MEAN) + lane;
              const float4 o = *mp;
              constexpr float inv = -1.0f / DM;
              *mp = make_float4(fmaf(t.x, inv, o.x), fmaf(t.y, inv, o.y), fmaf(t.z, inv, o.z), fmaf(t.w, inv, o.w));
              __syncwarp();
              mbar_arrive_if(BAR(BAR_STAT + 1), lane == 0);
              needm = false;
            }
            if (__all_sync(0xffffffffu, state == 2)) break;
            if (!__any_sync(0xffffffffu, polled)) __nanosleep(100);
            if (it > 4000000u) { asm volatile("st.global.u32 [%0], %1;" ::"l"(0ull), "r"(0) : "memory"); break; }
          }
        }
        if (!second) {
          int idx = CNT_AB + ((layer * 2 + m) * 16 + q * 4 + (lane & 3)) * 3 + (lane >> 2);
          uint32_t target = ep1 * 4;
          if (lane == 12 || lane == 13) idx = CNT_AB + ((layer * 2 + lane - 12) * 16 + r) * 3;
          if (lane == 14) { idx = CNT_XINIT + r; target = ep1 * 32; }
          uint32_t pend = lane < 15, pm = 0x7fff;
          mbar_wait(BAR(BAR_RG1 + 6), layer);
#pragma unroll 1
          for (uint32_t it = 0; pm; it++) {
            if (pend && (lane < 4 || !(pm & 15))) {
              uint32_t v;
              asm volatile("ld.acquire.gpu.global.u32 %0, [%1];" : "=r"(v) : "l"(&g_cnt[idx * CNT_STRIDE]) : "memory");
              if ((int32_t)(v - target) >= 0) {
                fence_async_all();
                if (lane < 4) mbar_arrive(BAR(BAR_ABOK + lane));
                if (layer == 0 && lane < 8) EV(120 + lane);
                pend = 0;
              }
            }
            const uint32_t nm = __ballot_sync(0xffffffffu, pend);
            mbar_arrive_if(BAR(BAR_AB1), lane == 0 && (pm & 0xf0) && !(nm & 0xf0));
            pm = nm;
            if (it > 2000000u) { asm volatile("st.global.u32 [%0], %1;" ::"l"(0ull), "r"(0) : "memory"); break; }
          }
          __syncwarp();
          mbar_arrive_if(BAR(BAR_FOK), lane == 0);
        }
      }
    } else {
      const CUtensorMap* mC = m ? &maps.ci : &maps.cr;
      const char* cbase = reinterpret_cast<const char*>((m ? cim : cre) + (size_t)(r * 128 + (lane >> 1)) * SEQ + q * 512) + (lane & 1) * 128;
      asm volatile("prefetch.global.L2 [%0];" ::"l"(cbase));
      const int myrow = r * 128 + p * 16 + (lane >> 1);
      if (lane < 16) {
#pragma unroll
        for (int i = 1; i < 3; i++) g_stat[i * SEQ + r * 128 + p * 16 + lane] = make_ulonglong2(0ull, 0ull);
      }
      auto cload = [&](int k) {
        if (elect_one()) {
          mbar_expect(BAR(BAR_CF + k), A_SLOT);
          tma2d_ef(sb + OFF_A + k * A_SLOT, mC, BAR(BAR_CF + k), q * 512 + k * 64, r * 128);
        }
        __syncwarp();
      };
      if (CPF_START >= 0) mbar_wait(BAR(BAR_XF + CPF_START), 0);
      uint32_t t0 = clock32();
      t0 += CL0_T0 + (cta & 3) * (CL0_DT / 4);
#pragma unroll 1
      for (int kc = 0; kc < 8; kc++) {
        if (kc == CL0_N) { mbar_wait(BAR(BAR_ABOK), 0); t0 = clock32() + (cta & 3) * (CL0_DT2 / 4); }
        spin_until(t0);
        t0 += kc < CL0_N ? CL0_DT : CL0_DT2;
        mbar_wait(BAR(kc < 7 ? BAR_RG1 + kc : BAR_A7), 0);
        cload(kc);
      }
      mbar_wait(BAR(BAR_EPOCH), 0);
      const uint32_t ep1 = *reinterpret_cast<volatile uint32_t*>(smem + OFF_EPOCH);
#pragma unroll 1
      for (int layer = 0; layer < 2; layer++) {
        if (layer) {
          if (elect_one()) {
#pragma unroll 1
            for (int kt = 0; kt < XEARLY4; kt++) {
              mbar_wait(BAR(BAR_XOK + kt), 0);
              mbar_wait(BAR(BAR_RG4 + kt), 0);
              if (kt == XG) mbar_wait(BAR(BAR_REL8), 0);
              if (kt == 0) t0 = clock32() + XLD_T0;
              spin_until(t0 + kt * XLD_DT);
              mbar_expect(BAR(BAR_XF + kt), A_SLOT);
              tma2d(sb + OFF_A + kt * A_SLOT, &maps.xld, BAR(BAR_XF + kt), kt * 64, r * 128);
              if (EVPH == 1) EV(80 + kt);
            }
          }
          __syncwarp();
          mbar_wait(BAR(CE1_BAR), CE1_PH);
          t0 = clock32() + (cta & 3) * (CE1_DT / 4);
#pragma unroll 1
          for (int kc = 0; kc < 8; kc++) {
            if (kc == CE1) { mbar_wait(BAR(BAR_STAT), 1); mbar_wait(BAR(BAR_ABOK), 1); }
            spin_until(t0);
            mbar_wait(BAR(kc < 7 ? BAR_RG1 + kc : BAR_A7), 1);
            if (kc < CE1) mbar_wait(BAR(BAR_RD + kc), 0);
            cload(kc);
            t0 = clock32() + (mbar_test(BAR(BAR_ABOK), 1) ? CLD_DT : CE1_DT);
          }
        }
        float s0 = 0.f, q0 = 0.f, s1 = 0.f, q1 = 0.f;
        const int lr = p * 16 + (lane >> 1);
        const uint32_t src = sb + OFF_A + lr * 128 + ((((lane & 1) * 4) ^ (lr & 7)) << 4);
#pragma unroll 1
        for (int k = 0; k < 9; k++) {
          if (k == 3) {
            mbar_wait(BAR(BAR_SENT), layer);
            if (lane == 0) { if (layer * 2 == EVPH) EV(39); cnt_arrive(CNT_X + (layer * 2 * 16 + r) * 9 + 7); if (layer * 2 == EVPH) EV(55); }
            __syncwarp();
          }
          if (k == 3) {
            if (layer == 0) cnt_wait(CNT_CS, ep1 * NHELP);
            float4 cs[5];
#pragma unroll
            for (int i = 0; i < 5; i++) cs[i] = __ldcg(reinterpret_cast<const float4*>(g_cs1 + p * 576) + min(lane + i * 32, 143));
#pragma unroll
            for (int i = 0; i < 5; i++) reinterpret_cast<float4*>(smem + OFF_CS1)[min(lane + i * 32, 143)] = cs[i];
            __syncwarp();
            mbar_arrive_if(BAR(BAR_CSOK), lane == 0);
          }
          if (lane == 0 && layer == 1 && k == 6) EV(31);
          mbar_wait(BAR(BAR_X1F + k), layer);
          if (lane == 0 && layer == 1 && k == 6) EV(30);
          uint4 v[4];
#pragma unroll
          for (int i = 0; i < 4; i++) v[i] = lds128((src ^ (i << 4)) + k * A_SLOT);
          sum8(v[0], s0, q0); sum8(v[1], s1, q1); sum8(v[2], s0, q0); sum8(v[3], s1, q1);
        }
        s0 += s1; q0 += q1;
        s0 += __shfl_xor_sync(0xffffffffu, s0, 1);
        q0 += __shfl_xor_sync(0xffffffffu, q0, 1);
        mbar_arrive_if(BAR(BAR_XRD), lane == 0);
        if (lane == 0 && layer == 1) EV(29);
        if (!(lane & 1)) stat_publish(&g_stat[(layer + 1) * SEQ + myrow], s0, q0, ep1);
        __syncwarp();
        stat_gather(&g_stat[(layer + 1) * SEQ + r * 128 + lane], ep1, reinterpret_cast<float*>(smem + OFF_RS) + lane, nullptr);
        __syncwarp();
        mbar_arrive_if(BAR(BAR_RSOK), lane == 0);
        if (layer == 0) {
          t0 = clock32();
#pragma unroll 1
          for (int i = 0; i < 32; i++) {
            pace(t0, i * CPF2_DT);
            asm volatile("prefetch.global.L2::evict_normal [%0];" ::"l"(cbase + (size_t)(i & 7) * 16 * SEQ * 2 + (i >> 3) * 256));
          }
        }
      }
    }
  } else {
    asm volatile("setmaxnreg.inc.sync.aligned.u32 232;");
    const uint32_t elect = (tid & 127) == 0;
    const uint32_t lane0 = lane == 0;
    if (wg == 1) {
      const int t = tid & 127;
      const int myrow = r * 128 + p * 16 + (t >> 3);
      const uint4* src = reinterpret_cast<const uint4*>(xin + (size_t)myrow * DM) + (t & 7);
      uint4* dst = reinterpret_cast<uint4*>(xout + (size_t)myrow * DM) + (t & 7);
      const int n = r * 9 + min(t >> 3, 8);
      const uint4* dsrc = reinterpret_cast<const uint4*>((m ? dim : dre) + (size_t)((n / 48) * 192 + q * 48 + n % 48) * DM) + (t & 7);
      float s = 0.f, qq = 0.f, sd = 0.f, s2 = 0.f, q2 = 0.f;
      uint4 v[3], d[3], vn[6], dn[6];
#pragma unroll
      for (int i = 0; i < 3; i++) { v[i] = __ldg(src + i * 8); d[i] = __ldg(dsrc + i * 8); }
#pragma unroll
      for (int i = 0; i < 6; i++) { vn[i] = __ldg(src + 24 + i * 8); dn[i] = __ldg(dsrc + 24 + i * 8); }
      START_SYNC();
#pragma unroll 1
      for (int it = 0; it < 72; it += 24) {
        sum8(v[0], s, qq); sum8(v[1], s2, q2); sum8(v[2], s, qq);
#pragma unroll
        for (int i = 0; i < 3; i++) {
          sd += ((bf_lo(d[i].x) + bf_hi(d[i].x)) + (bf_lo(d[i].y) + bf_hi(d[i].y))) + ((bf_lo(d[i].z) + bf_hi(d[i].z)) + (bf_lo(d[i].w) + bf_hi(d[i].w)));
          dst[it + i * 8] = v[i];
          v[i] = vn[i]; d[i] = dn[i]; vn[i] = vn[i + 3]; dn[i] = dn[i + 3];
        }
      }
      s += s2; qq += q2;
#pragma unroll
      for (int o = 1; o < 8; o <<= 1) {
        s += __shfl_xor_sync(0xffffffffu, s, o);
        qq += __shfl_xor_sync(0xffffffffu, qq, o);
        sd += __shfl_xor_sync(0xffffffffu, sd, o);
      }
      mbar_wait(BAR(BAR_EPOCH), 0);
      const uint32_t ep1 = *reinterpret_cast<volatile uint32_t*>(smem + OFF_EPOCH);
      if ((t & 7) == 0) {
        stat_publish(&g_stat[myrow], s, qq, ep1);
        if (t < 72) asm volatile("st.relaxed.gpu.global.u64 [%0], %1;" ::"l"(&g_csd[p * 144 + n]), "l"(((unsigned long long)ep1 << 32) | __float_as_uint(sd)) : "memory");
      }
      if (t < 32) g_rsum[(t >> 4) * SEQ + r * 128 + p * 16 + (t & 15)] = 0.f;
      EVE(118);
      __syncwarp();
      if (lane == 0) cnt_arrive(CNT_XINIT + r);
      asm volatile("bar.sync 2, 128;" ::: "memory");
    }

    const int srow = (lane & 7) + ((lane >> 3) & 1) * 8;
    const int schunk = lane >> 4;
    const int frow = warp * 16 + (lane >> 2);
    const uint32_t bfull = BAR(BAR_BFULL);
    const uint32_t bempty = map_rank(BAR(BAR_BEMPTY), lane & 1);
    const uint32_t elect2 = (tid & 127) < 2;
    constexpr uint32_t alo0 = ((sbd + OFF_A) >> 4) | (1u << 16);

#pragma unroll 1
    for (int layer = 0; layer < 2; layer++) {
      auto rowsums = [&](float (&rsum)[4]) {
#pragma unroll
        for (int i = 0; i < 4; i++) {
          rsum[i] += __shfl_xor_sync(0xffffffffu, rsum[i], 1);
          rsum[i] += __shfl_xor_sync(0xffffffffu, rsum[i], 2);
        }
        const int i = lane & 3;
        const float v = i == 0 ? rsum[0] : (i == 1 ? rsum[1] : (i == 2 ? rsum[2] : rsum[3]));
        asm volatile("red.global.add.f32 [%0], %1;" ::"l"(&g_rsum[layer * SEQ + r * 128 + frow + (i & 1) * 8 + (i >> 1) * 64]), "f"(v) : "memory");
      };
      auto flush = [&](auto& acc0, auto& acc1, auto na, int pi, int atom0) {
        constexpr int NA = decltype(na)::value;
        const int ffn = pi >= 7;
        const uint32_t fdone = BAR(BAR_FDONE + ffn * 9 + atom0);
        mbar_wait(BAR(BAR_FOK + ffn), layer);
        constexpr int HOFF = 2048;
        if (atom0) mbar_wait(fdone - 8, layer);
        else if (NA == 3) mbar_wait(BAR(BAR_A8), layer);
        const uint32_t stg = sb + (NA == 3 ? OFF_A + 8 * A_SLOT : OFF_STG) + warp * 4096;
        const uint32_t sad = stg + srow * 128;
        const uint32_t dt = NA == 3 ? (pi == 1 ? FLUSH_DT_A : FLUSH_DT) : (pi == 10 ? FLUSH_DT_D : (pi == 9 ? FLUSH_DT_E : FLUSH_DT4));
        float rs[4];
        if (NA == 3) {
#pragma unroll
          for (int i = 0; i < 4; i++) rs[i] = 0.f;
        } else {
          if (pi < 9) mbar_wait(BAR(BAR_RSOK), layer);
#pragma unroll
          for (int i = 0; i < 4; i++) rs[i] = lds32f(sb + OFF_RS + (frow + (i & 1) * 8 + (i >> 1) * 64) * 4);
        }
        uint32_t tn = clock32() + warp * (dt * STAGGER / 4);
#pragma unroll
        for (int n = 0; n < 2 * NA; n++) {
          uint32_t w[16];
#pragma unroll
          for (int j = 0; j < 16; j++) {
            const int o = (n >> 1) * 32 + j * 2;
            if (NA == 3) {
              w[j] = (n & 1) ? pk(acc1[o], acc1[o + 1]) : pk(acc0[o], acc0[o + 1]);
              rs[(n & 1) * 2 + (j & 1)] += (n & 1) ? acc1[o] + acc1[o + 1] : acc0[o] + acc0[o + 1];
            } else {
              const float f = rs[(n & 1) * 2 + (j & 1)];
              w[j] = (n & 1) ? pk(acc1[o] * f, acc1[o + 1] * f) : pk(acc0[o] * f, acc0[o + 1] * f);
            }
          }
#pragma unroll
          for (int j = 0; j < 4; j++)
            stsm4(sad + (n & 1) * HOFF + (((j * 2 + schunk) ^ (srow & 7)) << 4), w[j * 4], w[j * 4 + 1], w[j * 4 + 2], w[j * 4 + 3]);
          if (NA == 3 && n == 5) rowsums(rs);
          fence_async_smem();
          if (n > FRONT) tn += dt;
          spin_until(tn);
          __syncwarp();
          if (elect_one()) {
            tma_red2d(&maps.xred, stg + (n & 1) * HOFF, (atom0 + (n >> 1)) * 64, r * 128 + (n & 1) * 64 + warp * 16);
            bulk_commit();
            if (n == 2 * NA - 1) {
              bulk_wait0();
              mbar_arrive(fdone + 8 * (NA - 1));
            } else if (n) {
              asm volatile("cp.async.bulk.wait_group 1;" ::: "memory");
              if (!(n & 1)) mbar_arrive(fdone + 8 * ((n >> 1) - 1));
            }
          }
          __syncwarp();
        }
      };
      if (wg == 0) {
        float acc0[72], acc1[72];
        if (layer == 0) { START_SYNC(); TL(0); }
        constexpr uint32_t blo0 = ((sbd + OFF_B) >> 4) | (1u << 16);
        uint32_t ready = 0;
        auto step = [&](int s, auto first) {
          constexpr bool F = decltype(first)::value;
          if (!ready) {
            mbar_wait(BAR(BAR_XF + s), layer);
            mbar_wait(BAR(BAR_DF + s), layer);
            if (F && layer) mbar_wait(BAR(BAR_GO + 15), 0);
          }
          if (F) TL(1 + layer * 36);
          if (layer == 0) EVE(90 + s);
          const uint32_t alo = alo0 + s * (A_SLOT >> 4);
          const uint32_t blo = blo0 + (s & 3) * (D_SLOT >> 4);
          wg_fence();
#pragma unroll
          for (int k = 0; k < 4; k++) {
            if (F && k == 0) {
              wgmma_n144<0, true>(acc0, desc(alo, DESC_HI_128), desc(blo, DESC_HI_128));
              wgmma_n144<0, true>(acc1, desc(alo + 512, DESC_HI_128), desc(blo, DESC_HI_128));
            } else {
              wgmma_n144<0, false>(acc0, desc(alo + k * 2, DESC_HI_128), desc(blo + k * 2, DESC_HI_128));
              wgmma_n144<0, false>(acc1, desc(alo + 512 + k * 2, DESC_HI_128), desc(blo + k * 2, DESC_HI_128));
            }
          }
          wg_commit();
          ready = mbar_test(BAR(BAR_XF + s + 1), layer) & mbar_test(BAR(BAR_DF + min(s + 1, 8)), layer);
          if (!F) {
            wg_wait<1>();
            mbar_arrive_cl_if(bempty + 8 * (BAR_DREL - BAR_BEMPTY - 1 + s), elect2);
            mbar_arrive_if(BAR(BAR_RG1 - 1 + s), elect);
          }
        };
        step(0, TrueT{});
#pragma unroll 1
        for (int s = 1; s < 9; s++) step(s, FalseT{});
        mbar_arrive_if(BAR(BAR_GO), elect);
        asm volatile("bar.sync %0, 128;" ::"r"(1 + wg) : "memory");
        mbar_wait(BAR(BAR_CSD), 0);
        float2 cd[18];
#pragma unroll
        for (int i = 0; i < 18; i++) cd[i] = lds64f(sb + OFF_CSD + (i * 8 + (lane & 3) * 2) * 4);
        mbar_wait(BAR(BAR_STAT), layer);
        const float sg = m ? -1.f : 1.f;
        float2 st[4];
#pragma unroll
        for (int i = 0; i < 4; i++) {
          st[i].x = lds32f(sb + OFF_RS + (frow + (i & 1) * 8 + (i >> 1) * 64) * 4) * sg;
          st[i].y = lds32f(sb + OFF_MEAN + (frow + (i & 1) * 8 + (i >> 1) * 64) * 4);
        }
        wg_wait<0>();
        reg_fence(acc0); reg_fence(acc1);
        TL(2 + layer * 36);
        const uint32_t stg = sb + (warp * 16 + srow) * 96 + schunk * 16;
#pragma unroll
        for (int b2 = 0; b2 < 9; b2++) {
          const float2 c0 = cd[b2 * 2], c1 = cd[b2 * 2 + 1];
          const uint32_t ad = stg + (b2 < 3 ? OFF_STG : OFF_A + (6 + b2 / 3) * A_SLOT) + (b2 % 3) * 32;
          const int o = b2 * 8;
          stsm4(ad,
                pk(fmaf(c0.x, st[0].y, acc0[o]) * st[0].x, fmaf(c0.y, st[0].y, acc0[o + 1]) * st[0].x),
                pk(fmaf(c0.x, st[1].y, acc0[o + 2]) * st[1].x, fmaf(c0.y, st[1].y, acc0[o + 3]) * st[1].x),
                pk(fmaf(c1.x, st[0].y, acc0[o + 4]) * st[0].x, fmaf(c1.y, st[0].y, acc0[o + 5]) * st[0].x),
                pk(fmaf(c1.x, st[1].y, acc0[o + 6]) * st[1].x, fmaf(c1.y, st[1].y, acc0[o + 7]) * st[1].x));
          stsm4(ad + 64 * 96,
                pk(fmaf(c0.x, st[2].y, acc1[o]) * st[2].x, fmaf(c0.y, st[2].y, acc1[o + 1]) * st[2].x),
                pk(fmaf(c0.x, st[3].y, acc1[o + 2]) * st[3].x, fmaf(c0.y, st[3].y, acc1[o + 3]) * st[3].x),
                pk(fmaf(c1.x, st[2].y, acc1[o + 4]) * st[2].x, fmaf(c1.y, st[2].y, acc1[o + 5]) * st[2].x),
                pk(fmaf(c1.x, st[3].y, acc1[o + 6]) * st[3].x, fmaf(c1.y, st[3].y, acc1[o + 7]) * st[3].x));
          if (b2 == 2 || b2 == 8) {
            fence_async_smem();
            __syncwarp();
            mbar_arrive_if(BAR(BAR_ABSTG + (b2 == 8)), lane0);
          }
          if (b2 == 2) {
            asm volatile("bar.sync %0, 128;" ::"r"(1 + wg) : "memory");
            mbar_arrive_if(BAR(BAR_RG1 + 8), elect);
#pragma unroll
            for (int i = 0; i < NB + 1; i++) mbar_arrive_cl_if(bempty + 8 * i, elect2 && i + layer < NB + 1);
          }
        }
        TL(3 + layer * 36);
      }
#pragma unroll 1
      for (int pi = 2 - wg; pi < 12; pi += 2) {
        if (pi < 7) {
          float acc0[96], acc1[96];
          int atom0;
          int seq, nt, nt2 = 0, nt3 = 0, gap = 0, gap2 = 0, fbar, rbar = BAR_RNONE, sgm = pi;
          if (pi < 4) { atom0 = (pi - 1) * 3; nt = 8; seq = pi * 16 - 16; fbar = BAR_CF; if (pi == 3) rbar = BAR_RG2; }
          else if (pi == 4) { atom0 = 0; seq = 48; nt = G3A_C1 / 2; nt2 = (G3A_C2 - G3A_C1) / 2; nt3 = 9 - G3A_C2 / 2; gap = G3B_C1; gap2 = G3B_C2 - G3B_C1; fbar = BAR_X1F; }
          else if (pi == 5) { atom0 = 3; seq = 48 + G3A_C1; nt = G3B_C1 / 2; nt2 = (G3B_C2 - G3B_C1) / 2; nt3 = 9 - G3B_C2 / 2; gap = G3A_C2 - G3A_C1; gap2 = 18 - G3A_C2; fbar = BAR_X1F; rbar = BAR_RG3B; }
          else { atom0 = 6; seq = 84; nt = 9; fbar = BAR_X1F + 3; rbar = BAR_RG3C; sgm = 10; }
          constexpr uint32_t blo0 = ((sbd + OFF_B) >> 4) | ((4096u >> 4) << 16);
          uint32_t so = (seq % (NB + 1)) * 8, ph = seq / (NB + 1) + 1 - layer;
          uint32_t alo = alo0 + ((pi == 6) ? 6 * (A_SLOT >> 4) : 0);
          uint32_t fa = BAR(fbar), ra = BAR(rbar), go = BAR(BAR_GO + sgm);
          uint32_t pso, rel, epok = 0;
          auto issue = [&](uint32_t a, auto first) {
            constexpr bool F = decltype(first)::value;
            const uint32_t blo = blo0 + so * (B_SLOT >> 7);
            wg_fence();
            wgmma_n192<1, F>(acc0, desc(a, DESC_HI_128), desc(blo, DESC_HI_128));
            wgmma_n192<1, F>(acc1, desc(a + 512, DESC_HI_128), desc(blo, DESC_HI_128));
            wgmma_n192<1, false>(acc0, desc(a + 2, DESC_HI_128), desc(blo + 128, DESC_HI_128));
            wgmma_n192<1, false>(acc1, desc(a + 514, DESC_HI_128), desc(blo + 128, DESC_HI_128));
            wg_commit();
          };
          auto advance = [&]() { so += 8; if (so == (NB + 1) * 8) { so = 0; ph++; } };
          auto enter = [&]() {
            const uint32_t t0 = mbar_test(fa, layer), t1 = mbar_test(go - 8, layer), t2 = mbar_test(bfull + so, ph);
            if (!(t0 & t1 & t2)) {
              mbar_wait(fa, layer);
              mbar_wait(go - 8, layer);
              mbar_wait(bfull + so, ph);
            }
          };
          enter();
          TL(1 + pi * 3 + layer * 36);
          issue(alo, TrueT{});
          pso = so;
          advance();
          mbar_wait(bfull + so, ph);
#pragma unroll 1
          for (;;) {
            issue(alo + 4, FalseT{});
            const uint32_t cso = so;
            advance();
            alo += A_SLOT >> 4;
            if (alo == alo0 + 9 * (A_SLOT >> 4)) alo = alo0 + 3 * (A_SLOT >> 4);
            fa += 8;
            if (--nt == 0) {
              mbar_arrive_if(go, elect);
              wg_wait<1>();
              mbar_arrive_cl_if(bempty + pso, elect2);
              if (nt2 == 0 && pi >= 4) {
                const uint32_t t0 = mbar_test(BAR(BAR_STAT + 1), layer), t1 = mbar_test(BAR(BAR_CSOK), layer), t2 = mbar_test(BAR(BAR_RG3B + 2), layer);
                epok = t0 & t1 & t2;
              }
              wg_wait<0>();
              mbar_arrive_cl_if(bempty + cso, elect2);
              mbar_arrive_if(ra, elect);
              if (nt2 == 0) break;
              nt = nt2; nt2 = nt3; nt3 = 0;
              const uint32_t t = so + gap * 8;
              so = t % ((NB + 1) * 8); ph += t / ((NB + 1) * 8);
              gap = gap2;
              go += 16;
              rel = 0;
              enter();
            } else {
              const uint32_t ready = mbar_test(fa, layer) & mbar_test(bfull + so, ph);
              wg_wait<1>();
              mbar_arrive_cl_if(bempty + pso, elect2);
              rel = 1;
              if (!ready) {
                mbar_wait(fa, layer);
                mbar_wait(bfull + so, ph);
              }
            }
            issue(alo, FalseT{});
            pso = so;
            advance();
            const uint32_t ready = mbar_test(bfull + so, ph);
            wg_wait<1>();
            mbar_arrive_cl_if(bempty + cso, rel && elect2);
            mbar_arrive_if(ra, rel && elect);
            ra += 8;
            if (!ready) {
              mbar_wait(bfull + so, ph);
            }
          }
        wg_wait<0>();
        reg_fence(acc0); reg_fence(acc1);
        TL(2 + pi * 3 + layer * 36);
        if (pi >= 4 && pi <= 6) {
          if (!epok) {
            mbar_wait(BAR(BAR_STAT + 1), layer);
            mbar_wait(BAR(BAR_CSOK), layer);
            mbar_wait(BAR(BAR_RG3B + 2), layer);
          }
          if (pi == 5) mbar_wait(BAR(BAR_XRD), layer);
          if (pi == 6) asm volatile("bar.sync %0, 128;" ::"r"(1 + wg) : "memory");
          float2 st[4];
#pragma unroll
          for (int i = 0; i < 4; i++) st[i].y = lds32f(sb + OFF_MEAN + (frow + (i & 1) * 8 + (i >> 1) * 64) * 4);
          const uint32_t cs = sb + OFF_CS1 + (atom0 * 64 + (lane & 3) * 2) * 4;
          const uint32_t dst = sb + OFF_A + atom0 * A_SLOT + (warp * 16 + srow) * 128;
          float2 cn[2][2];
          cn[0][0] = lds64f(cs); cn[0][1] = lds64f(cs + 32); cn[1][0] = lds64f(cs + 64); cn[1][1] = lds64f(cs + 96);
#pragma unroll
          for (int b2 = 0; b2 < 12; b2++) {
            if ((b2 & 3) == 0 && pi == 5) mbar_wait(BAR(BAR_RG3C + 3 + (b2 >> 2)), layer);
            const float2 c0 = cn[b2 & 1][0], c1 = cn[b2 & 1][1];
            if (b2 + 2 < 12) { cn[b2 & 1][0] = lds64f(cs + (b2 + 2) * 64); cn[b2 & 1][1] = lds64f(cs + (b2 + 2) * 64 + 32); }
            const uint32_t ad = dst + (b2 >> 2) * A_SLOT + ((((b2 & 3) * 2 + schunk) ^ (srow & 7)) << 4);
            const int o = b2 * 8;
            stsm4(ad,
                  pk_relu(fmaf(c0.x, st[0].y, acc0[o]), fmaf(c0.y, st[0].y, acc0[o + 1])),
                  pk_relu(fmaf(c0.x, st[1].y, acc0[o + 2]), fmaf(c0.y, st[1].y, acc0[o + 3])),
                  pk_relu(fmaf(c1.x, st[0].y, acc0[o + 4]), fmaf(c1.y, st[0].y, acc0[o + 5])),
                  pk_relu(fmaf(c1.x, st[1].y, acc0[o + 6]), fmaf(c1.y, st[1].y, acc0[o + 7])));
            stsm4(ad + 8192,
                  pk_relu(fmaf(c0.x, st[2].y, acc1[o]), fmaf(c0.y, st[2].y, acc1[o + 1])),
                  pk_relu(fmaf(c0.x, st[3].y, acc1[o + 2]), fmaf(c0.y, st[3].y, acc1[o + 3])),
                  pk_relu(fmaf(c1.x, st[2].y, acc1[o + 4]), fmaf(c1.y, st[2].y, acc1[o + 5])),
                  pk_relu(fmaf(c1.x, st[3].y, acc1[o + 6]), fmaf(c1.y, st[3].y, acc1[o + 7])));
            if ((b2 & 3) == 3 && (pi == 6 || b2 == 11)) {
              fence_async_smem();
              __syncwarp();
              mbar_arrive_if(BAR(BAR_HF + atom0 + (b2 >> 2)), lane0);
              if (b2 == 11 && pi != 6) { mbar_arrive_if(BAR(BAR_HF + atom0), lane0); mbar_arrive_if(BAR(BAR_HF + atom0 + 1), lane0); }
            }
          }
        } else if (pi == 3) {
          asm volatile("bar.sync %0, 128;" ::"r"(1 + wg) : "memory");
          const uint32_t dst = sb + OFF_A + 6 * A_SLOT + (warp * 16 + srow) * 128;
          float rs[4] = {0.f, 0.f, 0.f, 0.f};
#pragma unroll
          for (int b2 = 0; b2 < 12; b2++) {
            if (b2 == 8) mbar_wait(BAR(BAR_FDONE + 5), layer);
            const uint32_t ad = dst + (b2 >> 2) * A_SLOT + ((((b2 & 3) * 2 + schunk) ^ (srow & 7)) << 4);
            const int o = b2 * 8;
            stsm4(ad, pk(acc0[o], acc0[o + 1]), pk(acc0[o + 2], acc0[o + 3]), pk(acc0[o + 4], acc0[o + 5]), pk(acc0[o + 6], acc0[o + 7]));
            stsm4(ad + 8192, pk(acc1[o], acc1[o + 1]), pk(acc1[o + 2], acc1[o + 3]), pk(acc1[o + 4], acc1[o + 5]), pk(acc1[o + 6], acc1[o + 7]));
            rs[0] += (acc0[o] + acc0[o + 1]) + (acc0[o + 4] + acc0[o + 5]);
            rs[1] += (acc0[o + 2] + acc0[o + 3]) + (acc0[o + 6] + acc0[o + 7]);
            rs[2] += (acc1[o] + acc1[o + 1]) + (acc1[o + 4] + acc1[o + 5]);
            rs[3] += (acc1[o + 2] + acc1[o + 3]) + (acc1[o + 6] + acc1[o + 7]);
            if ((b2 & 3) == 3) {
              fence_async_smem();
              __syncwarp();
              if (b2 == 3) {
                if (lane0) {
                  tma_red2d(&maps.xred, sb + OFF_A + 6 * A_SLOT + warp * 2048, 384, r * 128 + warp * 16);
                  tma_red2d(&maps.xred, sb + OFF_A + 6 * A_SLOT + 8192 + warp * 2048, 384, r * 128 + 64 + warp * 16);
                  bulk_commit();
                }
              } else {
                mbar_arrive_if(BAR(BAR_FDONE + 6 + (b2 >> 2)), lane0);
              }
            }
          }
          rowsums(rs);
          bulk_wait0();
          __syncwarp();
          mbar_arrive_if(BAR(BAR_FDONE + 6), lane0);
        } else {
          flush(acc0, acc1, IntT<3>{}, pi, atom0);
        }
        } else {
          auto hpass = [&](auto na) {
            constexpr int NA = decltype(na)::value, KU = 6 / NA, NS = 36 / KU;
            float a0[64], a1[NA == 2 ? 64 : 1];
            constexpr uint32_t blo0 = ((sbd + OFF_B) >> 4) | ((6144u >> 4) << 16);
            const int seq = (pi - 7) * 12;
            uint32_t so = (seq % NB) * 8, ph = seq / NB + layer, pso = 0;
            uint32_t ready = 0;
            auto step = [&](int s, auto first) {
              constexpr bool F = decltype(first)::value;
              if (F) {
                const uint32_t t0 = mbar_test(BAR(BAR_HF), layer), t1 = mbar_test(BAR(BAR_GO + 3 + pi), layer), t2 = mbar_test(bfull + so, ph);
                ready = t0 & t1 & t2;
              }
              if (!ready) {
                if (NA == 2) mbar_wait(BAR(BAR_HF + ((s * KU + KU - 1) >> 2)), layer);
                if (F) mbar_wait(BAR(BAR_GO + 3 + pi), layer);
                mbar_wait(bfull + so, ph);
              }
              if (F) TL(1 + pi * 3 + layer * 36);
              const uint32_t blo = blo0 + so * (B_SLOT >> 7);
              wg_fence();
#pragma unroll
              for (int j = 0; j < KU; j++) {
                const int u = s * KU + j;
                const uint64_t da0 = desc(alo0 + (u >> 2) * (A_SLOT >> 4) + (u & 3) * 2, DESC_HI_128);
                const uint64_t da1 = desc(alo0 + (u >> 2) * (A_SLOT >> 4) + (u & 3) * 2 + 512, DESC_HI_128);
                const uint64_t db = desc(blo + j * 128, DESC_HI_128);
                if constexpr (NA == 2) {
                  if (F && j == 0) { wgmma_n128<1, true>(a0, da0, db); wgmma_n128<1, true>(a1, da1, db); }
                  else { wgmma_n128<1, false>(a0, da0, db); wgmma_n128<1, false>(a1, da1, db); }
                } else {
                  if (F && j == 0) wgmma_n128<0, true, 1>(a0, db, da0);
                  else wgmma_n128<0, false, 1>(a0, db, da0);
                }
              }
              wg_commit();
              const uint32_t cso = so;
              so += 8;
              if (so == NB * 8) { so = 0; ph++; }
              mbar_arrive_if(BAR(BAR_GO + 4 + pi), elect && s == NS - 1);
              ready = mbar_test(bfull + so, ph);
              if (NA == 2) ready &= mbar_test(BAR(BAR_HF + ((s * KU + 2 * KU - 1) >> 2)), layer);
              if (!F) {
                wg_wait<1>();
                mbar_arrive_cl_if(bempty + pso, elect2);
                if (NA == 1) {
                  mbar_arrive_if(BAR(BAR_RG4 - 1 + ((6 * s) >> 2)), elect);
                  mbar_arrive_if(BAR(BAR_RG4 - 2 + ((6 * s) >> 2)), elect && !(s & 1));
                }
              }
              pso = cso;
            };
            float2 rsv[NA == 1 ? 16 : 1];
            if constexpr (NA == 1) {
#pragma unroll
              for (int i = 0; i < 16; i++) rsv[i] = lds64f(sb + OFF_RS + (i * 8 + (lane & 3) * 2) * 4);
            }
            step(0, TrueT{});
#pragma unroll 1
            for (int s = 1; s < NS; s++) step(s, FalseT{});
            wg_wait<0>();
            mbar_arrive_cl_if(bempty + pso, elect2);
            if (NA == 1) { mbar_arrive_if(BAR(BAR_RG4 + 7), elect); mbar_arrive_if(BAR(BAR_RG4 + 8), elect); }
            reg_fence(a0);
            TL(2 + pi * 3 + layer * 36);
            if constexpr (NA == 2) {
              reg_fence(a1);
              flush(a0, a1, na, pi, (pi - 7) * 2);
            } else {
              asm volatile("bar.sync %0, 128;" ::"r"(1 + wg) : "memory");
              const uint32_t tb = sb + OFF_A + 8 * A_SLOT;
              const uint32_t ad = tb + ((lane >> 4) * 8 + (lane & 7)) * 128 + (((warp * 2 + ((lane >> 3) & 1)) ^ (lane & 7)) << 4);
#pragma unroll
              for (int b2 = 0; b2 < 8; b2++) {
                const float2 f0 = rsv[b2 * 2], f1 = rsv[b2 * 2 + 1];
                const int o = b2 * 8;
                asm volatile("stmatrix.sync.aligned.m8n8.x4.trans.shared.b16 [%0], {%1,%2,%3,%4};" ::"r"(ad + b2 * 2048),
                             "r"(pk(a0[o] * f0.x, a0[o + 1] * f0.y)), "r"(pk(a0[o + 2] * f0.x, a0[o + 3] * f0.y)),
                             "r"(pk(a0[o + 4] * f1.x, a0[o + 5] * f1.y)), "r"(pk(a0[o + 6] * f1.x, a0[o + 7] * f1.y)));
              }
              fence_async_smem();
              __syncwarp();
              mbar_arrive_if(BAR(BAR_FDONE + 17), lane0);
              if (layer == 0) {
                const int row = tid & 127;
                const uint32_t ra = sb + OFF_A + row * 128 + ((row & 15) << 3);
                float s0 = 0.f, q0 = 0.f, s1 = 0.f, q1 = 0.f;
#pragma unroll 1
                for (int k = 0; k < 9; k++) {
                  mbar_wait(BAR(BAR_XF + k), 1);
                  uint4 v[8];
#pragma unroll
                  for (int i = 0; i < 8; i++) {
                    asm volatile("ld.shared.v2.u32 {%0,%1}, [%2];" : "=r"(v[i].x), "=r"(v[i].y) : "r"((ra ^ (i << 4)) + k * A_SLOT) : "memory");
                    asm volatile("ld.shared.v2.u32 {%0,%1}, [%2];" : "=r"(v[i].z), "=r"(v[i].w) : "r"((ra ^ ((i << 4) | 8)) + k * A_SLOT) : "memory");
                  }
#pragma unroll
                  for (int i = 0; i < 8; i += 2) { sum8(v[i], s0, q0); sum8(v[i + 1], s1, q1); }
                  if (k < CE1) {
                    asm volatile("bar.sync %0, 128;" ::"r"(1 + wg) : "memory");
                    mbar_arrive_if(BAR(BAR_RD + k), elect);
                  }
                }
                const float mean = (s0 + s1) * (1.0f / DM);
                reinterpret_cast<float*>(smem + OFF_RS)[row] = rsqrtf(fmaxf((q0 + q1) * (1.0f / DM) - mean * mean, 0.f) + 1e-5f);
                reinterpret_cast<float*>(smem + OFF_MEAN)[row] = -mean;
                asm volatile("bar.sync %0, 128;" ::"r"(1 + wg) : "memory");
                mbar_arrive_if(BAR(BAR_STAT), elect);
                EVE(25);
              }
            }
          };
          if (pi < 11) hpass(IntT<2>{}); else hpass(IntT<1>{});
        }
        TL(3 + pi * 3 + layer * 36);
      }
    }
  }
#undef BAR
}

typedef CUresult (*EncodeFn)(CUtensorMap*, CUtensorMapDataType, cuuint32_t, void*, const cuuint64_t*, const cuuint64_t*, const cuuint32_t*,
                             const cuuint32_t*, CUtensorMapInterleave, CUtensorMapSwizzle, CUtensorMapL2promotion, CUtensorMapFloatOOBfill);

void make2d(EncodeFn enc, CUtensorMap* m, const void* ptr, uint64_t inner, uint64_t outer, uint32_t bi, uint32_t bo, CUtensorMapSwizzle sw,
            CUtensorMapL2promotion pr = CU_TENSOR_MAP_L2_PROMOTION_L2_128B) {
  cuuint64_t d[2] = {inner, outer};
  cuuint64_t s[1] = {inner * 2};
  cuuint32_t b[2] = {bi, bo}, e[2] = {1, 1};
  enc(m, CU_TENSOR_MAP_DATA_TYPE_BFLOAT16, 2, const_cast<void*>(ptr), d, s, b, e, CU_TENSOR_MAP_INTERLEAVE_NONE, sw,
      pr, CU_TENSOR_MAP_FLOAT_OOB_FILL_NONE);
}
void make3d(EncodeFn enc, CUtensorMap* m, const void* ptr, uint64_t d0, uint64_t d1, uint64_t d2, uint64_t s1, uint64_t s2,
            uint32_t b0, uint32_t b1, uint32_t b2, CUtensorMapSwizzle sw) {
  cuuint64_t d[3] = {d0, d1, d2};
  cuuint64_t s[2] = {s1, s2};
  cuuint32_t b[3] = {b0, b1, b2}, e[3] = {1, 1, 1};
  enc(m, CU_TENSOR_MAP_DATA_TYPE_BFLOAT16, 3, const_cast<void*>(ptr), d, s, b, e, CU_TENSOR_MAP_INTERLEAVE_NONE, sw,
      CU_TENSOR_MAP_L2_PROMOTION_L2_128B, CU_TENSOR_MAP_FLOAT_OOB_FILL_NONE);
}

}

extern "C" void kernel_launch(void* const* d_in, const int* in_sizes, int n_in, void* d_out, int out_size) {
  (void)in_sizes; (void)n_in; (void)out_size;
  const __nv_bfloat16* x = (const __nv_bfloat16*)d_in[0];
  const __nv_bfloat16* cr = (const __nv_bfloat16*)d_in[1];
  const __nv_bfloat16* ci = (const __nv_bfloat16*)d_in[2];
  const __nv_bfloat16* dr = (const __nv_bfloat16*)d_in[3];
  const __nv_bfloat16* di = (const __nv_bfloat16*)d_in[4];
  const __nv_bfloat16* w1 = (const __nv_bfloat16*)d_in[6];
  const __nv_bfloat16* w2 = (const __nv_bfloat16*)d_in[7];
  __nv_bfloat16* out = (__nv_bfloat16*)d_out;

  void* fn = nullptr;
  cudaDriverEntryPointQueryResult qr;
  cudaGetDriverEntryPoint("cuTensorMapEncodeTiled", &fn, cudaEnableDefault, &qr);
  EncodeFn enc = (EncodeFn)fn;
  void* ab = nullptr;
  cudaGetSymbolAddress(&ab, g_ab);

  Maps maps;
  make2d(enc, &maps.xin, x, DM, SEQ, 64, 128, CU_TENSOR_MAP_SWIZZLE_128B, XPROMO);
  make2d(enc, &maps.xld, out, DM, SEQ, 64, 128, CU_TENSOR_MAP_SWIZZLE_128B);
  make2d(enc, &maps.xred, out, DM, SEQ, 64, 16, CU_TENSOR_MAP_SWIZZLE_128B);
  make2d(enc, &maps.cr, cr, SEQ, SEQ, 64, 128, CU_TENSOR_MAP_SWIZZLE_128B, CPROMO);
  make2d(enc, &maps.ci, ci, SEQ, SEQ, 64, 128, CU_TENSOR_MAP_SWIZZLE_128B, CPROMO);
  make3d(enc, &maps.dr, dr, DM, 192, 3, DM * 2, 192 * DM * 2, 64, 48, 3, CU_TENSOR_MAP_SWIZZLE_128B);
  make3d(enc, &maps.di, di, DM, 192, 3, DM * 2, 192 * DM * 2, 64, 48, 3, CU_TENSOR_MAP_SWIZZLE_128B);
  make3d(enc, &maps.abld, ab, 64, 4 * SEQ, DM / 64, DM * 2, 128, 64, 32, 3, CU_TENSOR_MAP_SWIZZLE_128B);
  make2d(enc, &maps.abst, ab, DM, 4 * SEQ, 48, 128, CU_TENSOR_MAP_SWIZZLE_NONE);
  make3d(enc, &maps.w1, w1, 64, DM, DFF / 64, DFF * 2, 128, 64, 32, 3, CU_TENSOR_MAP_SWIZZLE_128B);
  make3d(enc, &maps.w2, w2, 64, DFF, DM / 64, DM * 2, 128, 64, 48, 2, CU_TENSOR_MAP_SWIZZLE_128B);
  make3d(enc, &maps.w2n, w2, 64, DFF, DM / 64, DM * 2, 128, 64, 96, 1, CU_TENSOR_MAP_SWIZZLE_128B);

  cudaFuncSetAttribute(fnet_ffn_kernel, cudaFuncAttributeMaxDynamicSharedMemorySize, SMEM_BYTES);
  cudaLaunchConfig_t cfg = {};
  cfg.gridDim = dim3(NGRID);
  cfg.blockDim = dim3(384);
  cfg.dynamicSmemBytes = SMEM_BYTES;
  cfg.stream = cudaStreamPerThread;
  cudaLaunchAttribute at[1];
  at[0].id = cudaLaunchAttributeClusterDimension;
  at[0].val.clusterDim.x = CLUSTER; at[0].val.clusterDim.y = 1; at[0].val.clusterDim.z = 1;
  cfg.attrs = at;
  cfg.numAttrs = 1;
  cudaLaunchKernelEx(&cfg, fnet_ffn_kernel, maps, x, cr, ci, dr, di, w1, w2, out);
}
```

```cpp
#include <cuda_runtime.h>
#include <cuda_bf16.h>
#include <cuda.h>
#include <stdint.h>

namespace {

constexpr int SEQ = 2048, DM = 576, DFF = 4608;
constexpr int NHELP = 4, NWORK = 128, NGRID = NHELP + NWORK;

constexpr int A_SLOT = 16384, B_SLOT = 12288, NB = 5, D_SLOT = 18432;
constexpr int OFF_A = 0;
constexpr int OFF_B = 9 * A_SLOT;
constexpr int OFF_STG = OFF_B + NB * B_SLOT;
constexpr int OFF_CS1 = OFF_STG + 12288;
constexpr int OFF_CSD = OFF_STG + 16384;
constexpr int OFF_EPOCH = OFF_CSD + 576;
constexpr int OFF_RS = OFF_CSD + 640;
constexpr int OFF_BAR = OFF_RS + 512;
constexpr int SMEM_BYTES = 232448;

constexpr int BAR_HF = 0  , BAR_ABSTG = 9, BAR_FDONE = 11  ,
              BAR_BEMPTY = 32  , BAR_DREL = 38  , BAR_STGF = 46, BAR_STG2 = 47,
              BAR_CF = 48  , BAR_X1F = 56  ,
              BAR_RG1 = 68, BAR_RG2 = 77, BAR_RG3B = 86, BAR_RG3C = 95, BAR_RG4 = 104, BAR_RNONE = 113  ,
              BAR_STAT = 122  , BAR_FOK = 124  , BAR_EPOCH = 126, BAR_CSD = 127,
              BAR_XF = 128  , BAR_DF = 137  , BAR_ABOK = 146  , BAR_GO = 150  , BAR_XOK = 166  , BAR_SENT = 172,
              BAR_RSOK = 173, BAR_CSOK = 174, BAR_A7 = 175, BAR_RD = 176  , BAR_REL8 = 182, BAR_BFULL = 183  , BAR_A8 = 189, BAR_AB1 = 190, BAR_XRD = 191, NBAR = 192;
constexpr int OFF_MEAN = OFF_BAR + NBAR * 8;
constexpr int OFF_RS2 = OFF_MEAN + 512;
static_assert(OFF_RS2 % 16 == 0 && OFF_RS2 + 576 <= SMEM_BYTES, "smem");

constexpr int CNT_STRIDE = 32;
constexpr int CNT_AB = 0;
constexpr int CNT_X = 192;
constexpr int CNT_XINIT = CNT_X + 432;
constexpr int CNT_G3 = CNT_XINIT + 16;
constexpr int CNT_CS = CNT_G3 + 32;
constexpr int CNT_TICKET = CNT_CS + 1;
constexpr int NCNT = CNT_TICKET + 1;

__device__ uint32_t g_cnt[NCNT * CNT_STRIDE];
__device__ __align__(128) __nv_bfloat16 g_ab[2 * 2 * SEQ * DM];
__device__ __align__(16) float g_cs1[DFF];
__device__ __align__(16) float g_rsum[2 * SEQ];
__device__ __align__(16) unsigned long long g_csd[8 * 144];
__device__ ulonglong2 g_stat[3 * SEQ];

template <int V> struct IntT { static constexpr int value = V; };
struct TrueT { static constexpr bool value = true; };
struct FalseT { static constexpr bool value = false; };

struct Maps {
  CUtensorMap xin, xld, xred, cr, ci, dr, di, abld, abst, w1, w2, w2n;
};

template<int TB, bool FIRST, int TA = 0> __device__ __forceinline__ void wgmma_n128(float (&d)[64], uint64_t da, uint64_t db){
  if (FIRST) {
    asm volatile("wgmma.mma_async.sync.aligned.m64n128k16.f32.bf16.bf16 {%0, %1, %2, %3, %4, %5, %6, %7, %8, %9, %10, %11, %12, %13, %14, %15, %16, %17, %18, %19, %20, %21, %22, %23, %24, %25, %26, %27, %28, %29, %30, %31, %32, %33, %34, %35, %36, %37, %38, %39, %40, %41, %42, %43, %44, %45, %46, %47, %48, %49, %50, %51, %52, %53, %54, %55, %56, %57, %58, %59, %60, %61, %62, %63}, %64, %65, 0, 1, 1, %67, %66;"
     : "=f"(d[0]), "=f"(d[1]), "=f"(d[2]), "=f"(d[3]), "=f"(d[4]), "=f"(d[5]), "=f"(d[6]), "=f"(d[7]), "=f"(d[8]), "=f"(d[9]), "=f"(d[10]), "=f"(d[11]), "=f"(d[12]), "=f"(d[13]), "=f"(d[14]), "=f"(d[15]), "=f"(d[16]), "=f"(d[17]), "=f"(d[18]), "=f"(d[19]), "=f"(d[20]), "=f"(d[21]), "=f"(d[22]), "=f"(d[23]), "=f"(d[24]), "=f"(d[25]), "=f"(d[26]), "=f"(d[27]), "=f"(d[28]), "=f"(d[29]), "=f"(d[30]), "=f"(d[31]), "=f"(d[32]), "=f"(d[33]), "=f"(d[34]), "=f"(d[35]), "=f"(d[36]), "=f"(d[37]), "=f"(d[38]), "=f"(d[39]), "=f"(d[40]), "=f"(d[41]), "=f"(d[42]), "=f"(d[43]), "=f"(d[44]), "=f"(d[45]), "=f"(d[46]), "=f"(d[47]), "=f"(d[48]), "=f"(d[49]), "=f"(d[50]), "=f"(d[51]), "=f"(d[52]), "=f"(d[53]), "=f"(d[54]), "=f"(d[55]), "=f"(d[56]), "=f"(d[57]), "=f"(d[58]), "=f"(d[59]), "=f"(d[60]), "=f"(d[61]), "=f"(d[62]), "=f"(d[63])
     : "l"(da), "l"(db), "n"(TB), "n"(TA));
  } else {
    asm volatile("wgmma.mma_async.sync.aligned.m64n128k16.f32.bf16.bf16 {%0, %1, %2, %3, %4, %5, %6, %7, %8, %9, %10, %11, %12, %13, %14, %15, %16, %17, %18, %19, %20, %21, %22, %23, %24, %25, %26, %27, %28, %29, %30, %31, %32, %33, %34, %35, %36, %37, %38, %39, %40, %41, %42, %43, %44, %45, %46, %47, %48, %49, %50, %51, %52, %53, %54, %55, %56, %57, %58, %59, %60, %61, %62, %63}, %64, %65, 1, 1, 1, %67, %66;"
     : "+f"(d[0]), "+f"(d[1]), "+f"(d[2]), "+f"(d[3]), "+f"(d[4]), "+f"(d[5]), "+f"(d[6]), "+f"(d[7]), "+f"(d[8]), "+f"(d[9]), "+f"(d[10]), "+f"(d[11]), "+f"(d[12]), "+f"(d[13]), "+f"(d[14]), "+f"(d[15]), "+f"(d[16]), "+f"(d[17]), "+f"(d[18]), "+f"(d[19]), "+f"(d[20]), "+f"(d[21]), "+f"(d[22]), "+f"(d[23]), "+f"(d[24]), "+f"(d[25]), "+f"(d[26]), "+f"(d[27]), "+f"(d[28]), "+f"(d[29]), "+f"(d[30]), "+f"(d[31]), "+f"(d[32]), "+f"(d[33]), "+f"(d[34]), "+f"(d[35]), "+f"(d[36]), "+f"(d[37]), "+f"(d[38]), "+f"(d[39]), "+f"(d[40]), "+f"(d[41]), "+f"(d[42]), "+f"(d[43]), "+f"(d[44]), "+f"(d[45]), "+f"(d[46]), "+f"(d[47]), "+f"(d[48]), "+f"(d[49]), "+f"(d[50]), "+f"(d[51]), "+f"(d[52]), "+f"(d[53]), "+f"(d[54]), "+f"(d[55]), "+f"(d[56]), "+f"(d[57]), "+f"(d[58]), "+f"(d[59]), "+f"(d[60]), "+f"(d[61]), "+f"(d[62]), "+f"(d[63])
     : "l"(da), "l"(db), "n"(TB), "n"(TA));
  }
}
template<int TB, bool FIRST, int TA = 0> __device__ __forceinline__ void wgmma_n144(float (&d)[72], uint64_t da, uint64_t db){
  if (FIRST) {
    asm volatile("wgmma.mma_async.sync.aligned.m64n144k16.f32.bf16.bf16 {%0, %1, %2, %3, %4, %5, %6, %7, %8, %9, %10, %11, %12, %13, %14, %15, %16, %17, %18, %19, %20, %21, %22, %23, %24, %25, %26, %27, %28, %29, %30, %31, %32, %33, %34, %35, %36, %37, %38, %39, %40, %41, %42, %43, %44, %45, %46, %47, %48, %49, %50, %51, %52, %53, %54, %55, %56, %57, %58, %59, %60, %61, %62, %63, %64, %65, %66, %67, %68, %69, %70, %71}, %72, %73, 0, 1, 1, %75, %74;"
     : "=f"(d[0]), "=f"(d[1]), "=f"(d[2]), "=f"(d[3]), "=f"(d[4]), "=f"(d[5]), "=f"(d[6]), "=f"(d[7]), "=f"(d[8]), "=f"(d[9]), "=f"(d[10]), "=f"(d[11]), "=f"(d[12]), "=f"(d[13]), "=f"(d[14]), "=f"(d[15]), "=f"(d[16]), "=f"(d[17]), "=f"(d[18]), "=f"(d[19]), "=f"(d[20]), "=f"(d[21]), "=f"(d[22]), "=f"(d[23]), "=f"(d[24]), "=f"(d[25]), "=f"(d[26]), "=f"(d[27]), "=f"(d[28]), "=f"(d[29]), "=f"(d[30]), "=f"(d[31]), "=f"(d[32]), "=f"(d[33]), "=f"(d[34]), "=f"(d[35]), "=f"(d[36]), "=f"(d[37]), "=f"(d[38]), "=f"(d[39]), "=f"(d[40]), "=f"(d[41]), "=f"(d[42]), "=f"(d[43]), "=f"(d[44]), "=f"(d[45]), "=f"(d[46]), "=f"(d[47]), "=f"(d[48]), "=f"(d[49]), "=f"(d[50]), "=f"(d[51]), "=f"(d[52]), "=f"(d[53]), "=f"(d[54]), "=f"(d[55]), "=f"(d[56]), "=f"(d[57]), "=f"(d[58]), "=f"(d[59]), "=f"(d[60]), "=f"(d[61]), "=f"(d[62]), "=f"(d[63]), "=f"(d[64]), "=f"(d[65]), "=f"(d[66]), "=f"(d[67]), "=f"(d[68]), "=f"(d[69]), "=f"(d[70]), "=f"(d[71])
     : "l"(da), "l"(db), "n"(TB), "n"(TA));
  } else {
    asm volatile("wgmma.mma_async.sync.aligned.m64n144k16.f32.bf16.bf16 {%0, %1, %2, %3, %4, %5, %6, %7, %8, %9, %10, %11, %12, %13, %14, %15, %16, %17, %18, %19, %20, %21, %22, %23, %24, %25, %26, %27, %28, %29, %30, %31, %32, %33, %34, %35, %36, %37, %38, %39, %40, %41, %42, %43, %44, %45, %46, %47, %48, %49, %50, %51, %52, %53, %54, %55, %56, %57, %58, %59, %60, %61, %62, %63, %64, %65, %66, %67, %68, %69, %70, %71}, %72, %73, 1, 1, 1, %75, %74;"
     : "+f"(d[0]), "+f"(d[1]), "+f"(d[2]), "+f"(d[3]), "+f"(d[4]), "+f"(d[5]), "+f"(d[6]), "+f"(d[7]), "+f"(d[8]), "+f"(d[9]), "+f"(d[10]), "+f"(d[11]), "+f"(d[12]), "+f"(d[13]), "+f"(d[14]), "+f"(d[15]), "+f"(d[16]), "+f"(d[17]), "+f"(d[18]), "+f"(d[19]), "+f"(d[20]), "+f"(d[21]), "+f"(d[22]), "+f"(d[23]), "+f"(d[24]), "+f"(d[25]), "+f"(d[26]), "+f"(d[27]), "+f"(d[28]), "+f"(d[29]), "+f"(d[30]), "+f"(d[31]), "+f"(d[32]), "+f"(d[33]), "+f"(d[34]), "+f"(d[35]), "+f"(d[36]), "+f"(d[37]), "+f"(d[38]), "+f"(d[39]), "+f"(d[40]), "+f"(d[41]), "+f"(d[42]), "+f"(d[43]), "+f"(d[44]), "+f"(d[45]), "+f"(d[46]), "+f"(d[47]), "+f"(d[48]), "+f"(d[49]), "+f"(d[50]), "+f"(d[51]), "+f"(d[52]), "+f"(d[53]), "+f"(d[54]), "+f"(d[55]), "+f"(d[56]), "+f"(d[57]), "+f"(d[58]), "+f"(d[59]), "+f"(d[60]), "+f"(d[61]), "+f"(d[62]), "+f"(d[63]), "+f"(d[64]), "+f"(d[65]), "+f"(d[66]), "+f"(d[67]), "+f"(d[68]), "+f"(d[69]), "+f"(d[70]), "+f"(d[71])
     : "l"(da), "l"(db), "n"(TB), "n"(TA));
  }
}
template<int TB, bool FIRST, int TA = 0> __device__ __forceinline__ void wgmma_n192(float (&d)[96], uint64_t da, uint64_t db){
  if (FIRST) {
    asm volatile("wgmma.mma_async.sync.aligned.m64n192k16.f32.bf16.bf16 {%0, %1, %2, %3, %4, %5, %6, %7, %8, %9, %10, %11, %12, %13, %14, %15, %16, %17, %18, %19, %20, %21, %22, %23, %24, %25, %26, %27, %28, %29, %30, %31, %32, %33, %34, %35, %36, %37, %38, %39, %40, %41, %42, %43, %44, %45, %46, %47, %48, %49, %50, %51, %52, %53, %54, %55, %56, %57, %58, %59, %60, %61, %62, %63, %64, %65, %66, %67, %68, %69, %70, %71, %72, %73, %74, %75, %76, %77, %78, %79, %80, %81, %82, %83, %84, %85, %86, %87, %88, %89, %90, %91, %92, %93, %94, %95}, %96, %97, 0, 1, 1, %99, %98;"
     : "=f"(d[0]), "=f"(d[1]), "=f"(d[2]), "=f"(d[3]), "=f"(d[4]), "=f"(d[5]), "=f"(d[6]), "=f"(d[7]), "=f"(d[8]), "=f"(d[9]), "=f"(d[10]), "=f"(d[11]), "=f"(d[12]), "=f"(d[13]), "=f"(d[14]), "=f"(d[15]), "=f"(d[16]), "=f"(d[17]), "=f"(d[18]), "=f"(d[19]), "=f"(d[20]), "=f"(d[21]), "=f"(d[22]), "=f"(d[23]), "=f"(d[24]), "=f"(d[25]), "=f"(d[26]), "=f"(d[27]), "=f"(d[28]), "=f"(d[29]), "=f"(d[30]), "=f"(d[31]), "=f"(d[32]), "=f"(d[33]), "=f"(d[34]), "=f"(d[35]), "=f"(d[36]), "=f"(d[37]), "=f"(d[38]), "=f"(d[39]), "=f"(d[40]), "=f"(d[41]), "=f"(d[42]), "=f"(d[43]), "=f"(d[44]), "=f"(d[45]), "=f"(d[46]), "=f"(d[47]), "=f"(d[48]), "=f"(d[49]), "=f"(d[50]), "=f"(d[51]), "=f"(d[52]), "=f"(d[53]), "=f"(d[54]), "=f"(d[55]), "=f"(d[56]), "=f"(d[57]), "=f"(d[58]), "=f"(d[59]), "=f"(d[60]), "=f"(d[61]), "=f"(d[62]), "=f"(d[63]), "=f"(d[64]), "=f"(d[65]), "=f"(d[66]), "=f"(d[67]), "=f"(d[68]), "=f"(d[69]), "=f"(d[70]), "=f"(d[71]), "=f"(d[72]), "=f"(d[73]), "=f"(d[74]), "=f"(d[75]), "=f"(d[76]), "=f"(d[77]), "=f"(d[78]), "=f"(d[79]), "=f"(d[80]), "=f"(d[81]), "=f"(d[82]), "=f"(d[83]), "=f"(d[84]), "=f"(d[85]), "=f"(d[86]), "=f"(d[87]), "=f"(d[88]), "=f"(d[89]), "=f"(d[90]), "=f"(d[91]), "=f"(d[92]), "=f"(d[93]), "=f"(d[94]), "=f"(d[95])
     : "l"(da), "l"(db), "n"(TB), "n"(TA));
  } else {
    asm volatile("wgmma.mma_async.sync.aligned.m64n192k16.f32.bf16.bf16 {%0, %1, %2, %3, %4, %5, %6, %7, %8, %9, %10, %11, %12, %13, %14, %15, %16, %17, %18, %19, %20, %21, %22, %23, %24, %25, %26, %27, %28, %29, %30, %31, %32, %33, %34, %35, %36, %37, %38, %39, %40, %41, %42, %43, %44, %45, %46, %47, %48, %49, %50, %51, %52, %53, %54, %55, %56, %57, %58, %59, %60, %61, %62, %63, %64, %65, %66, %67, %68, %69, %70, %71, %72, %73, %74, %75, %76, %77, %78, %79, %80, %81, %82, %83, %84, %85, %86, %87, %88, %89, %90, %91, %92, %93, %94, %95}, %96, %97, 1, 1, 1, %99, %98;"
     : "+f"(d[0]), "+f"(d[1]), "+f"(d[2]), "+f"(d[3]), "+f"(d[4]), "+f"(d[5]), "+f"(d[6]), "+f"(d[7]), "+f"(d[8]), "+f"(d[9]), "+f"(d[10]), "+f"(d[11]), "+f"(d[12]), "+f"(d[13]), "+f"(d[14]), "+f"(d[15]), "+f"(d[16]), "+f"(d[17]), "+f"(d[18]), "+f"(d[19]), "+f"(d[20]), "+f"(d[21]), "+f"(d[22]), "+f"(d[23]), "+f"(d[24]), "+f"(d[25]), "+f"(d[26]), "+f"(d[27]), "+f"(d[28]), "+f"(d[29]), "+f"(d[30]), "+f"(d[31]), "+f"(d[32]), "+f"(d[33]), "+f"(d[34]), "+f"(d[35]), "+f"(d[36]), "+f"(d[37]), "+f"(d[38]), "+f"(d[39]), "+f"(d[40]), "+f"(d[41]), "+f"(d[42]), "+f"(d[43]), "+f"(d[44]), "+f"(d[45]), "+f"(d[46]), "+f"(d[47]), "+f"(d[48]), "+f"(d[49]), "+f"(d[50]), "+f"(d[51]), "+f"(d[52]), "+f"(d[53]), "+f"(d[54]), "+f"(d[55]), "+f"(d[56]), "+f"(d[57]), "+f"(d[58]), "+f"(d[59]), "+f"(d[60]), "+f"(d[61]), "+f"(d[62]), "+f"(d[63]), "+f"(d[64]), "+f"(d[65]), "+f"(d[66]), "+f"(d[67]), "+f"(d[68]), "+f"(d[69]), "+f"(d[70]), "+f"(d[71]), "+f"(d[72]), "+f"(d[73]), "+f"(d[74]), "+f"(d[75]), "+f"(d[76]), "+f"(d[77]), "+f"(d[78]), "+f"(d[79]), "+f"(d[80]), "+f"(d[81]), "+f"(d[82]), "+f"(d[83]), "+f"(d[84]), "+f"(d[85]), "+f"(d[86]), "+f"(d[87]), "+f"(d[88]), "+f"(d[89]), "+f"(d[90]), "+f"(d[91]), "+f"(d[92]), "+f"(d[93]), "+f"(d[94]), "+f"(d[95])
     : "l"(da), "l"(db), "n"(TB), "n"(TA));
  }
}

__device__ __forceinline__ uint32_t clock32() { uint32_t t; asm volatile("mov.u32 %0, %%clock;" : "=r"(t)); return t; }
__device__ __forceinline__ bool elect_one() {
  uint32_t pred;
  asm volatile("{\n.reg .pred p;\nelect.sync _|p, 0xffffffff;\nselp.u32 %0, 1, 0, p;\n}" : "=r"(pred));
  return pred != 0;
}
__device__ __forceinline__ void mbar_init(uint32_t b, int c) { asm volatile("mbarrier.init.shared::cta.b64 [%0], %1;" ::"r"(b), "r"(c) : "memory"); }
__device__ __forceinline__ void mbar_expect(uint32_t b, int bytes) { asm volatile("mbarrier.arrive.expect_tx.shared::cta.b64 _, [%0], %1;" ::"r"(b), "r"(bytes) : "memory"); }
__device__ __forceinline__ void mbar_arrive(uint32_t b) { asm volatile("mbarrier.arrive.shared::cta.b64 _, [%0];" ::"r"(b) : "memory"); }
__device__ __forceinline__ void mbar_arrive_if(uint32_t b, uint32_t pred) {
  asm volatile("{\n.reg .pred p;\nsetp.ne.u32 p, %1, 0;\n@p mbarrier.arrive.shared::cta.b64 _, [%0];\n}" ::"r"(b), "r"(pred) : "memory");
}
#define WAIT_LIMIT "2000000"
#define DIE_ADDR "l"(0ull)
#define DIE_ST "st.global.u32 [%2], %1;\n"
__device__ __forceinline__ void die() { asm volatile("st.global.u32 [%0], %1;" ::"l"(0ull), "r"(0) : "memory"); }
__device__ __forceinline__ void mbar_wait(uint32_t b, uint32_t ph) {
  asm volatile(
      "{\n.reg .pred p;\n.reg .u32 c;\nmov.u32 c, 0;\n"
      "W:\nmbarrier.try_wait.parity.shared::cta.b64 p, [%0], %1, 1000;\n@p bra D;\n"
      "add.u32 c, c, 1;\nsetp.lt.u32 p, c, " WAIT_LIMIT ";\n@p bra W;\n" DIE_ST
      "D:\n}" ::"r"(b), "r"(ph), DIE_ADDR : "memory");
}
__device__ __forceinline__ uint32_t mbar_test(uint32_t b, uint32_t ph) {
  uint32_t ok;
  asm volatile("{\n.reg .pred p;\nmbarrier.test_wait.parity.shared::cta.b64 p, [%1], %2;\nselp.u32 %0, 1, 0, p;\n}" : "=r"(ok) : "r"(b), "r"(ph) : "memory");
  return ok;
}
__device__ __forceinline__ void cnt_arrive(int idx) {
  asm volatile("red.release.gpu.global.add.u32 [%0], 1;" ::"l"(&g_cnt[idx * CNT_STRIDE]) : "memory");
}
__device__ __forceinline__ void cnt_wait(uint32_t idx, uint32_t target) {
  asm volatile(
      "{\n.reg .pred p;\n.reg .u32 c, v;\nmov.u32 c, 0;\n"
      "W:\nld.acquire.gpu.global.u32 v, [%3];\nsub.u32 v, v, %1;\nsetp.ge.s32 p, v, 0;\n@p bra D;\n"
      "add.u32 c, c, 1;\nsetp.lt.u32 p, c, " WAIT_LIMIT ";\n@p bra W;\n" DIE_ST
      "D:\n}" ::"r"(idx | 0x80000000u), "r"(target), DIE_ADDR, "l"(&g_cnt[idx * CNT_STRIDE]) : "memory");
}
__device__ __forceinline__ void release_x(uint32_t fdone, uint32_t ph, int cnt, int n, uint32_t mask) {
#pragma unroll 1
  for (int k = 0; k < n;) {
    int e = k + __ffs(mask >> k);
    mbar_wait(fdone + 8 * (e - 1), ph);
    asm volatile("fence.release.gpu;" ::: "memory");
    asm volatile("red.relaxed.gpu.global.add.u32 [%0], 1;" ::"l"(&g_cnt[(cnt + e - 1) * CNT_STRIDE]) : "memory");
    k = e;
  }
}
__device__ __forceinline__ uint4 lds128(uint32_t a) {
  uint4 v;
  asm volatile("ld.shared.v4.u32 {%0,%1,%2,%3}, [%4];" : "=r"(v.x), "=r"(v.y), "=r"(v.z), "=r"(v.w) : "r"(a) : "memory");
  return v;
}
__device__ __forceinline__ void stat_publish(ulonglong2* p, float s, float qq, uint32_t ep1) {
  const float mean = s * (1.0f / DM);
  const float rstd = rsqrtf(fmaxf(qq * (1.0f / DM) - mean * mean, 0.f) + 1e-5f);
  const unsigned long long tag = (unsigned long long)ep1 << 32;
  asm volatile("st.relaxed.gpu.global.v2.u64 [%0], {%1, %2};" ::"l"(p), "l"(tag | __float_as_uint(rstd)), "l"(tag | __float_as_uint(-mean)) : "memory");
}
__device__ __forceinline__ void stat_gather(const ulonglong2* p, uint32_t tag, float* rsd, float* md, float* rs2) {
  unsigned long long a[4], b[4];
#pragma unroll 1
  for (uint32_t it = 0;; it++) {
    bool ok = true;
#pragma unroll
    for (int i = 0; i < 4; i++) asm volatile("ld.relaxed.gpu.global.v2.u64 {%0, %1}, [%2];" : "=l"(a[i]), "=l"(b[i]) : "l"(p + i * 32) : "memory");
#pragma unroll
    for (int i = 0; i < 4; i++) ok = ok && (uint32_t)(a[i] >> 32) == tag && (uint32_t)(b[i] >> 32) == tag;
    if (ok) break;
    if (it > 2000000u) { die(); break; }
  }
#pragma unroll
  for (int i = 0; i < 4; i++) {
    rsd[(i & 1) * 64 + (i >> 1) * 2] = __uint_as_float((uint32_t)a[i]);
    if (md) md[(i & 1) * 64 + (i >> 1) * 2] = __uint_as_float((uint32_t)b[i]);
    if (rs2) rs2[i * 8] = __uint_as_float((uint32_t)a[i]);
  }
}
__device__ __forceinline__ void pace(uint32_t t0, uint32_t dt) { while (clock32() - t0 < dt) __nanosleep(20); }
__device__ __forceinline__ void spin_until(uint32_t t) {
  asm volatile("{\n.reg .pred p;\n.reg .u32 c;\nW:\nmov.u32 c, %%clock;\nsub.u32 c, c, %0;\nsetp.lt.s32 p, c, 0;\n@p nanosleep.u32 40;\n@p bra W;\n}" ::"r"(t) : "memory");
}
__device__ __forceinline__ void tma2d(uint32_t dst, const CUtensorMap* m, uint32_t bar, int c0, int c1) {
  asm volatile("cp.async.bulk.tensor.2d.shared::cluster.global.mbarrier::complete_tx::bytes [%0], [%1, {%3, %4}], [%2];" ::"r"(dst), "l"(m), "r"(bar), "r"(c0), "r"(c1) : "memory");
}
__device__ __forceinline__ void tma2d_ef(uint32_t dst, const CUtensorMap* m, uint32_t bar, int c0, int c1) {
  asm volatile("{\n.reg .b64 pol;\ncreatepolicy.fractional.L2::evict_first.b64 pol, 1.0;\n"
               "cp.async.bulk.tensor.2d.shared::cluster.global.mbarrier::complete_tx::bytes.L2::cache_hint [%0], [%1, {%3, %4}], [%2], pol;\n}"
               ::"r"(dst), "l"(m), "r"(bar), "r"(c0), "r"(c1) : "memory");
}
__device__ __forceinline__ void tma3d(uint32_t dst, const CUtensorMap* m, uint32_t bar, int c0, int c1, int c2) {
  asm volatile("cp.async.bulk.tensor.3d.shared::cluster.global.mbarrier::complete_tx::bytes [%0], [%1, {%3, %4, %5}], [%2];" ::"r"(dst), "l"(m), "r"(bar), "r"(c0), "r"(c1), "r"(c2) : "memory");
}
__device__ __forceinline__ void tma3d_mc(uint32_t dst, const CUtensorMap* m, uint32_t bar, int c0, int c1, int c2) {
  asm volatile("cp.async.bulk.tensor.3d.shared::cluster.global.mbarrier::complete_tx::bytes.multicast::cluster [%0], [%1, {%3, %4, %5}], [%2], %6;"
               ::"r"(dst), "l"(m), "r"(bar), "r"(c0), "r"(c1), "r"(c2), "h"((uint16_t)3) : "memory");
}
__device__ __forceinline__ uint32_t map_rank(uint32_t a, uint32_t rank) {
  uint32_t v;
  asm("mapa.shared::cluster.u32 %0, %1, %2;" : "=r"(v) : "r"(a), "r"(rank));
  return v;
}
__device__ __forceinline__ void mbar_arrive_cl_if(uint32_t b, uint32_t pred) {
  asm volatile("{\n.reg .pred p;\nsetp.ne.u32 p, %1, 0;\n@p mbarrier.arrive.shared::cluster.b64 _, [%0];\n}" ::"r"(b), "r"(pred) : "memory");
}
__device__ __forceinline__ void bulk_pf(const void* p, int bytes) {
  asm volatile("cp.async.bulk.prefetch.L2.global [%0], %1;" ::"l"(p), "r"(bytes) : "memory");
}
__device__ __forceinline__ void tma_st2d(const CUtensorMap* m, uint32_t src, int c0, int c1) {
  asm volatile("cp.async.bulk.tensor.2d.global.shared::cta.tile.bulk_group [%0, {%2, %3}], [%1];" ::"l"(m), "r"(src), "r"(c0), "r"(c1) : "memory");
}
__device__ __forceinline__ void tma_red2d(const CUtensorMap* m, uint32_t src, int c0, int c1) {
  asm volatile("cp.reduce.async.bulk.tensor.2d.global.shared::cta.add.tile.bulk_group [%0, {%2, %3}], [%1];" ::"l"(m), "r"(src), "r"(c0), "r"(c1) : "memory");
}
__device__ __forceinline__ void bulk_commit() { asm volatile("cp.async.bulk.commit_group;" ::: "memory"); }
__device__ __forceinline__ void bulk_wait0() { asm volatile("cp.async.bulk.wait_group 0;" ::: "memory"); }
__device__ __forceinline__ void fence_async_smem() { asm volatile("fence.proxy.async.shared::cta;" ::: "memory"); }
__device__ __forceinline__ void fence_async_global() { asm volatile("fence.proxy.async.global;" ::: "memory"); }
__device__ __forceinline__ void wg_fence() { asm volatile("wgmma.fence.sync.aligned;" ::: "memory"); }
__device__ __forceinline__ void wg_commit() { asm volatile("wgmma.commit_group.sync.aligned;" ::: "memory"); }
template <int N> __device__ __forceinline__ void wg_wait() { asm volatile("wgmma.wait_group.sync.aligned %0;" ::"n"(N) : "memory"); }
__device__ __forceinline__ uint32_t pk(float a, float b) {
  uint32_t r;
  asm("cvt.rn.bf16x2.f32 %0, %1, %2;" : "=r"(r) : "f"(b), "f"(a));
  return r;
}
__device__ __forceinline__ uint32_t pk_relu(float a, float b) {
  uint32_t r;
  asm("cvt.rn.relu.bf16x2.f32 %0, %1, %2;" : "=r"(r) : "f"(b), "f"(a));
  return r;
}
__device__ __forceinline__ float bf_lo(uint32_t v) { return __uint_as_float(v << 16); }
__device__ __forceinline__ float bf_hi(uint32_t v) { return __uint_as_float(v & 0xffff0000u); }
__device__ __forceinline__ void stsm4(uint32_t addr, uint32_t a0, uint32_t a1, uint32_t a2, uint32_t a3) {
  asm volatile("stmatrix.sync.aligned.m8n8.x4.shared.b16 [%0], {%1,%2,%3,%4};" ::"r"(addr), "r"(a0), "r"(a1), "r"(a2), "r"(a3));
}
template <int R> __device__ __forceinline__ void reg_fence(float (&d)[R]) {
#pragma unroll
  for (int i = 0; i < R; i++) asm volatile("" : "+f"(d[i])::"memory");
}
constexpr uint32_t DESC_HI_128 = (1024u >> 4) | (1u << 30);
__device__ __forceinline__ uint64_t desc(uint32_t lo, uint32_t hi) {
  uint64_t d;
  asm("mov.b64 %0, {%1, %2};" : "=l"(d) : "r"(lo), "r"(hi));
  return d;
}

__device__ __forceinline__ void sum8(uint4 v, float& s, float& q) {
  float a;
  a = bf_lo(v.x); s += a; q = fmaf(a, a, q);  a = bf_hi(v.x); s += a; q = fmaf(a, a, q);
  a = bf_lo(v.y); s += a; q = fmaf(a, a, q);  a = bf_hi(v.y); s += a; q = fmaf(a, a, q);
  a = bf_lo(v.z); s += a; q = fmaf(a, a, q);  a = bf_hi(v.z); s += a; q = fmaf(a, a, q);
  a = bf_lo(v.w); s += a; q = fmaf(a, a, q);  a = bf_hi(v.w); s += a; q = fmaf(a, a, q);
}

__device__ __forceinline__ int frag_pos(int row) { return (((row >> 4) & 3) * 8 + (row & 7)) * 4 + ((row >> 3) & 1) + (row >> 6) * 2; }
__device__ __forceinline__ float4 lds128f(uint32_t a) {
  float4 v;
  asm volatile("ld.shared.v4.f32 {%0,%1,%2,%3}, [%4];" : "=f"(v.x), "=f"(v.y), "=f"(v.z), "=f"(v.w) : "r"(a) : "memory");
  return v;
}

constexpr int G3A_C1 = 8;
constexpr int G3B_C1 = 6;
constexpr int G3A_C2 = 12;
constexpr int G3B_C2 = 10;
constexpr int CLD_DT = 900;
constexpr int FLUSH_DT = 800;
constexpr int FLUSH_DT_D = 450;
constexpr int CPF2_DT = 400;
constexpr int HPF_D_START = 78000;
constexpr int HW1_START = 10000;
constexpr int XEARLY4 = 6;
constexpr int FLUSH_DT4 = 870;
constexpr int RELMASK2 = 0x1AC;
constexpr int RELMASK4 = 0x12A;
constexpr int FLUSH_DT_A = 800;
constexpr int AG_DT = 200;
constexpr int CL0_T0 = 1000;
constexpr int REST_T0 = 700;
constexpr int CE1 = 4;
constexpr int CE1_DT = 1300;
constexpr int CL0_DT = 1250;
constexpr int CL0_DT2 = 1000;
constexpr int CL0_N = 6;
constexpr int DG = 5;
constexpr int X2_DT = 700;
constexpr int X2_DT2 = 300;
constexpr int FLUSH_DT_E = 820;

__global__ void __launch_bounds__(384, 1)
fnet_ffn_kernel(const __grid_constant__ Maps maps, const __nv_bfloat16* __restrict__ xin, const __nv_bfloat16* __restrict__ cre,
                const __nv_bfloat16* __restrict__ cim, const __nv_bfloat16* __restrict__ dre,
                const __nv_bfloat16* __restrict__ dim, const __nv_bfloat16* __restrict__ w2,
                __nv_bfloat16* xout) {
  extern __shared__ __align__(1024) unsigned char smem[];
  const uint32_t sb = __shfl_sync(0xffffffffu, (uint32_t)__cvta_generic_to_shared(smem), 0);
  constexpr uint32_t sbd = 1024;
  const int tid = threadIdx.x;
  const int wg = __shfl_sync(0xffffffffu, tid >> 7, 0);
  const int warp = __shfl_sync(0xffffffffu, (tid >> 5) & 3, 0);
  const int lane = tid & 31;
  if (blockIdx.x < NHELP) {
    if (tid == 0) atomicAdd(&g_cnt[CNT_TICKET * CNT_STRIDE], 1u);
    const uint32_t th0 = clock32();
    constexpr int HS = 16, HG = DFF / 192 / NHELP;
    const uint32_t hb = sb + HS * B_SLOT + 8192;
    if (tid == 0) {
#pragma unroll
      for (int i = 0; i < 2 * HS; i++) mbar_init(hb + 8 * i, 1);
      asm volatile("fence.mbarrier_init.release.cluster;" ::: "memory");
    }
    for (int i = tid; i < 2048; i += 384) reinterpret_cast<uint32_t*>(smem + HS * B_SLOT)[i] = 0x3f803f80u;
    fence_async_smem();
    __syncthreads();
    if (wg == 0) {
      int slot = 0, ph = 0;
#pragma unroll 1
      for (int g = 0; g < HG; g++) {
        float acc[96];
#pragma unroll
        for (int i = 0; i < 96; i++) acc[i] = 0.f;
#pragma unroll 1
        for (int st = 0; st < 18; st++) {
          mbar_wait(hb + 8 * slot, ph);
          const uint32_t blo = (((sbd + slot * B_SLOT) >> 4) | ((4096u >> 4) << 16));
          const uint64_t da = desc(((sbd + HS * B_SLOT) >> 4) | (1u << 16), DESC_HI_128);
          wg_fence();
          wgmma_n192<1, false>(acc, da, desc(blo, DESC_HI_128));
          wgmma_n192<1, false>(acc, da, desc(blo + 128, DESC_HI_128));
          wg_commit();
          wg_wait<1>();
          mbar_arrive_if(hb + 8 * (HS + ((slot + HS - 1) & (HS - 1))), tid == 0 && (g | st));
          if (++slot == HS) { slot = 0; ph ^= 1; }
        }
        wg_wait<0>();
        reg_fence(acc);
        if (tid < 4) {
#pragma unroll
          for (int b = 0; b < 24; b++)
            *reinterpret_cast<float2*>(g_cs1 + ((blockIdx.x * HG + g) / 3) * 576 + tid * 144 + (g % 3) * 48 + b * 2) = make_float2(acc[b * 4], acc[b * 4 + 1]);
        }
      }
      __syncwarp();
      if (tid == 0) { cnt_arrive(CNT_CS); }
    } else if (tid == 128) {
      int slot = 0, ph = 1;
      pace(th0, HW1_START);
#pragma unroll 1
      for (int i = 0; i < HG * 18; i++) {
        mbar_wait(hb + 8 * (HS + slot), ph);
        mbar_expect(hb + 8 * slot, B_SLOT);
        tma3d(sb + slot * B_SLOT, &maps.w1, hb + 8 * slot, 0, (i % 18) * 32, (blockIdx.x * HG + i / 18) * 3);
        if (++slot == HS) { slot = 0; ph ^= 1; }
      }
      constexpr int W2N = DM * DFF * 2 / NHELP / 8192;
#pragma unroll 1
      for (int i = 0; i < W2N; i++) bulk_pf(reinterpret_cast<const char*>(w2) + (size_t)(blockIdx.x * W2N + i) * 8192, 8192);
      pace(th0, HPF_D_START);
#pragma unroll 1
      for (int i = 0; i < 81; i++) bulk_pf(reinterpret_cast<const char*>((blockIdx.x & 1) ? dim : dre) + ((blockIdx.x >> 1) * 81 + i) * 4096, 4096);
    }
    return;
  }
  const int cta = blockIdx.x - NHELP;
  const int r = cta & 15, p = cta >> 4;
  const int m = p >> 2, q = p & 3;
  const int rank = cta & 1;
  const uint32_t bar0 = sb + OFF_BAR;
#define BAR(i) (bar0 + 8u * (uint32_t)(i))
#define START_SYNC() do { __syncwarp(); asm volatile("barrier.cluster.wait.acquire.aligned;" ::: "memory"); } while (0)

  uint32_t ticket = 0;
  if (elect_one()) {
    const int w12 = wg * 4 + warp;
#pragma unroll
    for (int i = 0; i < 16; i++) mbar_init(BAR(w12 * 16 + i), w12 < 2 ? 4 : (w12 == 2 ? 2 : 1));
    asm volatile("fence.mbarrier_init.release.cluster;" ::: "memory");
    if (w12 == 8) {
      fence_async_smem();
      mbar_expect(BAR(BAR_XF), A_SLOT);
      tma2d(sb + OFF_A, &maps.xin, BAR(BAR_XF), 0, r * 128);
    }
  }
  __syncwarp();
  asm volatile("barrier.cluster.arrive.relaxed.aligned;" ::: "memory");
  if (wg == 2 && warp == 0) {
    START_SYNC();
    if (elect_one()) {
#pragma unroll 1
      for (int k = 0; k < 4; k++) {
        mbar_expect(BAR(BAR_DF + k), D_SLOT);
        if ((k & 1) == rank) tma3d_mc(sb + OFF_B + k * D_SLOT, m ? &maps.di : &maps.dr, BAR(BAR_DF + k), k * 64, q * 48, 0);
        mbar_expect(BAR(BAR_XF + k + 1), A_SLOT);
        tma2d(sb + OFF_A + (k + 1) * A_SLOT, &maps.xin, BAR(BAR_XF + k + 1), (k + 1) * 64, r * 128);
      }
    }
    __syncwarp();
  }
  if (tid == 320) asm volatile("atom.relaxed.gpu.global.add.u32 %0, [%1], 1;" : "=r"(ticket) : "l"(&g_cnt[CNT_TICKET * CNT_STRIDE]));

  if (wg == 2) {
    asm volatile("setmaxnreg.dec.sync.aligned.u32 40;");
    if (warp & 1) START_SYNC();
    if (warp == 0) {
      const CUtensorMap* mD = m ? &maps.di : &maps.dr;
      if (elect_one()) {
        int slot = 0, ph = 1;
#pragma unroll 1
        for (int layer = 0; layer < 2; layer++) {
#pragma unroll 1
          for (int s = 0; s < 9; s++) {
            if (s < 3) {
              const int nacq = layer ? (s == 0 ? 3 : 1) : 2;
#pragma unroll 1
              for (int i = 0; i < nacq; i++) {
                mbar_wait(BAR(BAR_BEMPTY + slot), ph);
                mbar_arrive(BAR(BAR_BFULL + slot));
                if (++slot == NB + 1 - layer) { slot = 0; ph ^= 1; }
              }
            } else if (s == 3) {
              if (layer) {
                mbar_wait(BAR(BAR_FDONE + 16), 0);
                mbar_arrive_cl_if(map_rank(BAR(BAR_STGF), 0), 1);
                mbar_arrive_cl_if(map_rank(BAR(BAR_STGF), 1), 1);
                mbar_wait(BAR(BAR_STGF), 0);
              }
            } else {
              mbar_wait(BAR(BAR_DREL + s - 4), layer);
            }
            if (layer && s == DG) mbar_wait(BAR(BAR_REL8), 0);
            if (layer || s >= 4) {
              mbar_expect(BAR(BAR_DF + s), D_SLOT);
              if ((s & 1) == rank) tma3d_mc(sb + OFF_B + (s & 3) * D_SLOT, mD, BAR(BAR_DF + s), s * 64, q * 48, 0);
              const int k = s + 1;
              if (layer == 0 && k < 9) {
                mbar_expect(BAR(BAR_XF + k), A_SLOT);
                tma2d(sb + OFF_A + k * A_SLOT, &maps.xin, BAR(BAR_XF + k), k * 64, r * 128);
              }
            }
          }
          if (layer) {
            mbar_wait(BAR(BAR_BEMPTY + slot), ph);
            mbar_arrive(BAR(BAR_BFULL + slot));
            mbar_arrive_cl_if(map_rank(BAR(BAR_BEMPTY + slot), 0), 1);
            mbar_arrive_cl_if(map_rank(BAR(BAR_BEMPTY + slot), 1), 1);
            slot = 0; ph ^= 1;
          }
#pragma unroll 1
          for (int sg = -2; sg < 18; sg++) {
            const CUtensorMap* mm;
            int row, atom, n, dk = 32;
            if (sg < 4) {
              mm = &maps.abld; row = (layer * 2 + m) * SEQ + q * 512;
              if (sg < 2) { mbar_wait(BAR(BAR_ABOK + sg + 2), layer); row += (sg + 2) * 128; atom = 0; n = 4; }
              else { mbar_wait(BAR(sg == 2 ? BAR_AB1 : BAR_FOK), layer); atom = (sg - 1) * 3; n = 16; }
            } else if (sg < 13) {
              mm = &maps.w1;
              if (sg < 10) {
                const int cw = sg & 1;
                const int c1 = cw ? G3B_C1 : G3A_C1, c2 = cw ? G3B_C2 : G3A_C2;
                const int lo = sg < 6 ? 0 : (sg < 8 ? c1 : c2), hi = sg < 6 ? c1 : (sg < 8 ? c2 : 18);
                atom = p * 9 + cw * 3; row = lo * 32; n = hi - lo;
              } else { atom = p * 9 + 6; row = (12 - sg) * 192; n = 6; }
            } else {
              row = p * 576;
              atom = (sg - 13) * 2;
              if (sg < 17) { mm = &maps.w2; n = 12; dk = 48; }
              else { mm = &maps.w2n; n = 6; dk = 96; }
            }
            const uint32_t fb0 = BAR(BAR_BFULL);
            const int nsl = sg < 13 ? NB + 1 : NB;
            if (sg == -1) mbar_wait(BAR(BAR_STG2), layer);
#pragma unroll 1
            for (int i = 0; i < n; i++) {
              mbar_wait(BAR(BAR_BEMPTY + slot), ph);
              mbar_expect(fb0 + 8 * slot, B_SLOT);
              if ((i & 1) == rank) tma3d_mc(sb + OFF_B + slot * B_SLOT, mm, fb0 + 8 * slot, 0, row, atom);
              row += dk;
              if (++slot == nsl) { slot = 0; ph ^= 1; }
            }
          }
        }
#pragma unroll 1
        for (int i = 0; i < NB; i++) {
          mbar_wait(BAR(BAR_BEMPTY + slot), ph);
          if (++slot == NB) { slot = 0; ph ^= 1; }
        }
      }
    } else if (warp == 1) {
      if (lane == 0) {
        asm volatile("prefetch.tensormap [%0];" ::"l"(m ? &maps.ci : &maps.cr) : "memory");
        asm volatile("prefetch.tensormap [%0];" ::"l"(&maps.abst) : "memory");
        asm volatile("prefetch.tensormap [%0];" ::"l"(&maps.abld) : "memory");
      }
      mbar_wait(BAR(BAR_EPOCH), 0);
      const uint32_t ep1 = *reinterpret_cast<volatile uint32_t*>(smem + OFF_EPOCH);
      {
        unsigned long long a[3], b[3];
#pragma unroll 1
        for (uint32_t it = 0;; it++) {
          bool ok = true;
#pragma unroll
          for (int i = 0; i < 3; i++)
            asm volatile("ld.relaxed.gpu.global.v2.u64 {%0, %1}, [%2];" : "=l"(a[i]), "=l"(b[i]) : "l"(&g_csd[p * 144 + min(lane + i * 32, 71) * 2]) : "memory");
#pragma unroll
          for (int i = 0; i < 3; i++) ok = ok && (uint32_t)(a[i] >> 32) == ep1 && (uint32_t)(b[i] >> 32) == ep1;
          if (ok) break;
          if (it > 2000000u) { die(); break; }
        }
#pragma unroll
        for (int i = 0; i < 3; i++)
          reinterpret_cast<float2*>(smem + OFF_CSD)[(min(lane + i * 32, 71) & 3) * 18 + (min(lane + i * 32, 71) >> 2)] = make_float2(__uint_as_float((uint32_t)a[i]), __uint_as_float((uint32_t)b[i]));
        __syncwarp();
        mbar_arrive_if(BAR(BAR_CSD), lane == 0);
      }
      if (lane == 0) {
#pragma unroll 1
        for (int layer = 0; layer < 2; layer++) {
          const int abrow = (layer * 2 + m) * SEQ + r * 128;
          const int abcnt = CNT_AB + ((layer * 2 + m) * 16 + r) * 3;
          mbar_wait(BAR(BAR_ABSTG), layer);
          mbar_wait(BAR(BAR_ABOK), layer);
          spin_until(clock32() + REST_T0);
          tma_st2d(&maps.abst, sb + OFF_A + 7 * A_SLOT, 192 + q * 48, abrow);
          bulk_commit();
          bulk_wait0();
          mbar_arrive(BAR(BAR_A7));
          cnt_arrive(abcnt + 1);
          tma_st2d(&maps.abst, sb + OFF_A + 8 * A_SLOT, 384 + q * 48, abrow);
          bulk_commit();
          bulk_wait0();
          mbar_arrive(BAR(BAR_A8));
          cnt_arrive(abcnt + 2);
          release_x(BAR(BAR_FDONE), layer, CNT_X + (layer * 2 * 16 + r) * 9, 6, RELMASK2);
          {
            uint32_t tn = 0;
#pragma unroll 1
            for (int i = 0; i < 8; i++) {
              if ((i & 3) == 0) mbar_wait(BAR(BAR_FDONE + 7 + (i >> 2)), layer);
              if (i == 0) tn = clock32();
              spin_until(tn);
              tma_red2d(&maps.xred, sb + OFF_A + 7 * A_SLOT + i * 4096, 448 + (i >> 2) * 64, r * 128 + (i & 3) * 32);
              tma_red2d(&maps.xred, sb + OFF_A + 7 * A_SLOT + i * 4096 + 2048, 448 + (i >> 2) * 64, r * 128 + (i & 3) * 32 + 16);
              tn += AG_DT;
              if (i == 3) {
                bulk_commit();
                mbar_wait(BAR(BAR_FDONE + 6), layer);
                bulk_wait0();
                mbar_arrive(BAR(BAR_SENT));
              }
            }
            bulk_commit();
            bulk_wait0();
            cnt_arrive(CNT_X + (layer * 2 * 16 + r) * 9 + 8);
          }
          mbar_wait(BAR(BAR_XRD), layer);
#pragma unroll 1
          for (int s = 0; s < 3; s++) {
            mbar_wait(BAR(BAR_RG3C + s), layer);
            mbar_wait(BAR(BAR_RG3B + 6 + s), layer);
            mbar_expect(BAR(BAR_X1F + 9 + s), A_SLOT);
            tma2d(sb + OFF_A + (6 + s) * A_SLOT, &maps.xld, BAR(BAR_X1F + 9 + s), s * 64, r * 128);
          }
#pragma unroll 1
          for (int s = 0; s < 3; s++) mbar_wait(BAR(BAR_X1F + 9 + s), layer);
          cnt_arrive(CNT_G3 + layer * 16 + r);
          cnt_wait(CNT_G3 + layer * 16 + r, ep1 * 8);
          mbar_arrive(BAR(BAR_FOK + 1));
          if (layer == 0) release_x(BAR(BAR_FDONE + 9), 0, CNT_X + (16 + r) * 9, 6, RELMASK4);
          mbar_wait(BAR(BAR_FDONE + 17), layer);
          tma_red2d(&maps.xld, sb + OFF_A + 8 * A_SLOT, 512, r * 128);
          bulk_commit();
          bulk_wait0();
          if (layer == 0) {
            mbar_wait(BAR(BAR_FDONE + 16), 0);
            asm volatile("fence.release.gpu;" ::: "memory");
            asm volatile("red.relaxed.gpu.global.add.u32 [%0], 1;" ::"l"(&g_cnt[(CNT_X + (16 + r) * 9 + 8) * CNT_STRIDE]) : "memory");
            mbar_arrive(BAR(BAR_REL8));
          }
        }
      }
    } else if (warp == 2) {
      START_SYNC();
      if ((sb & 0x3FFFFu) != sbd) die();
      const uint32_t ep1 = __shfl_sync(0xffffffffu, ticket, 0) / NGRID + 1;
      if (lane == 0) {
        *reinterpret_cast<volatile uint32_t*>(smem + OFF_EPOCH) = ep1;
        mbar_arrive(BAR(BAR_EPOCH));
      }
      {
        stat_gather(&g_stat[r * 128 + lane], ep1, reinterpret_cast<float*>(smem + OFF_RS) + frag_pos(lane), reinterpret_cast<float*>(smem + OFF_MEAN) + frag_pos(lane), nullptr);
        __syncwarp();
        mbar_arrive_if(BAR(BAR_STAT), lane == 0);
      }
#pragma unroll 1
      for (int ph4 = 0; ph4 < 4; ph4++) {
        const int layer = ph4 >> 1, second = ph4 & 1;
        if (ph4) {
          const int pl = (ph4 - 1) >> 1, k = min(lane, 8);
          const uint32_t fd = BAR(BAR_FDONE + (second ? 0 : 9));
          const uint32_t fr = BAR(second ? (k < 8 ? BAR_RG2 + k : BAR_RG1 + 8) : BAR_RG4 + k);
          const uint32_t fb = BAR((second ? BAR_X1F : BAR_XF) + k);
          const int kr = k - 1 + __ffs((second ? RELMASK2 : RELMASK4) >> k);
          const uint32_t* flag = &g_cnt[(CNT_X + ((ph4 - 1) * 16 + r) * 9 + kr) * CNT_STRIDE];
          uint32_t state = lane >= 9 ? 2 : 0;
          bool needm = second;
          uint32_t tgo = 0;
          if (second) mbar_wait(BAR(BAR_STAT), layer);
          mbar_wait(fd, pl);
#pragma unroll 1
          for (uint32_t it = 0;; it++) {
            bool polled = false;
            if (state == 0 && mbar_test(fd + 8 * kr, pl)) {
              uint32_t c;
              asm volatile("ld.acquire.gpu.global.u32 %0, [%1];" : "=r"(c) : "l"(flag) : "memory");
              polled = true;
              if ((int32_t)(c - ep1 * 8) >= 0) {
                fence_async_global();
                state = 1;
                tgo = clock32() + (second ? (k < 3 ? k * X2_DT : (kr - k < 2 && k < 8 && k > 3 ? (1 - (kr - k)) * X2_DT2 : 0)) : 0);
                if (!second && k < XEARLY4) { mbar_arrive(BAR(BAR_XOK + k)); state = 2; }
              }
            }
            if (state == 1 && (int32_t)(clock32() - tgo) >= 0 && mbar_test(fr, pl)) {
              mbar_expect(fb, A_SLOT);
              tma2d(sb + OFF_A + k * A_SLOT, &maps.xld, fb, k * 64, r * 128);
              state = 2;
            }
            if (needm && (__ballot_sync(0xffffffffu, state != 0) & 0xff) == 0xff) {
              __syncwarp();
              float4 t;
              asm volatile("ld.relaxed.gpu.global.v4.f32 {%0,%1,%2,%3}, [%4];" : "=f"(t.x), "=f"(t.y), "=f"(t.z), "=f"(t.w) : "l"(&g_rsum[layer * SEQ + r * 128 + lane * 4]) : "memory");
              float4* mp = reinterpret_cast<float4*>(smem + OFF_MEAN) + lane;
              const float4 o = *mp;
              constexpr float inv = -1.0f / DM;
              *mp = make_float4(fmaf(t.x, inv, o.x), fmaf(t.y, inv, o.y), fmaf(t.z, inv, o.z), fmaf(t.w, inv, o.w));
              __syncwarp();
              mbar_arrive_if(BAR(BAR_STAT + 1), lane == 0);
              needm = false;
            }
            if (__all_sync(0xffffffffu, state == 2)) break;
            if (!__any_sync(0xffffffffu, polled)) __nanosleep(100);
            if (it > 4000000u) { die(); break; }
          }
        }
        if (!second) {
          int idx = CNT_AB + ((layer * 2 + m) * 16 + q * 4 + (lane & 3)) * 3 + (lane >> 2);
          uint32_t target = ep1 * ((lane < 4 || lane >= 12) ? 16 : 4);
          if (lane == 12 || lane == 13) idx = CNT_AB + ((layer * 2 + lane - 12) * 16 + r) * 3;
          if (lane == 14) { idx = CNT_XINIT + r; target = ep1 * 32; }
          uint32_t pend = lane < 15, pm = 0x7fff;
          mbar_wait(BAR(BAR_RG1 + 6), layer);
#pragma unroll 1
          for (uint32_t it = 0; pm; it++) {
            if (pend && (lane < 4 || !(pm & 15))) {
              uint32_t v;
              asm volatile("ld.acquire.gpu.global.u32 %0, [%1];" : "=r"(v) : "l"(&g_cnt[idx * CNT_STRIDE]) : "memory");
              if ((int32_t)(v - target) >= 0) {
                fence_async_global();
                if (lane < 4) mbar_arrive(BAR(BAR_ABOK + lane));
                pend = 0;
              }
            }
            __syncwarp();
            const uint32_t nm = __ballot_sync(0xffffffffu, pend);
            mbar_arrive_if(BAR(BAR_AB1), lane == 0 && (pm & 0xf0) && !(nm & 0xf0));
            pm = nm;
            if (it > 2000000u) { die(); break; }
          }
          __syncwarp();
          mbar_arrive_if(BAR(BAR_FOK), lane == 0);
        }
      }
    } else {
      const CUtensorMap* mC = m ? &maps.ci : &maps.cr;
      const char* cbase = reinterpret_cast<const char*>((m ? cim : cre) + (size_t)(r * 128 + (lane >> 1)) * SEQ + q * 512) + (lane & 1) * 128;
      asm volatile("prefetch.global.L2 [%0];" ::"l"(cbase));
      const int myrow = r * 128 + p * 16 + (lane >> 1);
      auto cload = [&](int k) {
        if (elect_one()) {
          mbar_expect(BAR(BAR_CF + k), A_SLOT);
          tma2d_ef(sb + OFF_A + k * A_SLOT, mC, BAR(BAR_CF + k), q * 512 + k * 64, r * 128);
        }
        __syncwarp();
      };
      uint32_t t0 = clock32() + CL0_T0 + (cta & 3) * (CL0_DT / 4);
#pragma unroll 1
      for (int kc = 0; kc < 8; kc++) {
        if (kc == CL0_N) { mbar_wait(BAR(BAR_ABOK), 0); t0 = clock32() + (cta & 3) * (CL0_DT2 / 4); }
        spin_until(t0);
        t0 += kc < CL0_N ? CL0_DT : CL0_DT2;
        mbar_wait(BAR(kc < 7 ? BAR_RG1 + kc : BAR_A7), 0);
        cload(kc);
      }
      mbar_wait(BAR(BAR_EPOCH), 0);
      const uint32_t ep1 = *reinterpret_cast<volatile uint32_t*>(smem + OFF_EPOCH);
#pragma unroll 1
      for (int layer = 0; layer < 2; layer++) {
        if (layer) {
          if (elect_one()) {
#pragma unroll 1
            for (int kt = 0; kt < XEARLY4; kt++) {
              mbar_wait(BAR(BAR_XOK + kt), 0);
              mbar_wait(BAR(BAR_RG4 + kt), 0);
              mbar_expect(BAR(BAR_XF + kt), A_SLOT);
              tma2d(sb + OFF_A + kt * A_SLOT, &maps.xld, BAR(BAR_XF + kt), kt * 64, r * 128);
            }
          }
          __syncwarp();
          mbar_wait(BAR(BAR_REL8), 0);
          t0 = clock32() + (cta & 3) * (CE1_DT / 4);
#pragma unroll 1
          for (int kc = 0; kc < 8; kc++) {
            if (kc == CE1) { mbar_wait(BAR(BAR_STAT), 1); mbar_wait(BAR(BAR_ABOK), 1); }
            spin_until(t0);
            mbar_wait(BAR(kc < 7 ? BAR_RG1 + kc : BAR_A7), 1);
            if (kc < CE1) mbar_wait(BAR(BAR_RD + kc), 0);
            cload(kc);
            t0 = clock32() + (mbar_test(BAR(BAR_ABOK), 1) ? CLD_DT : CE1_DT);
          }
        }
        float s0 = 0.f, q0 = 0.f, s1 = 0.f, q1 = 0.f;
        const int lr = p * 16 + (lane >> 1);
        const uint32_t src = sb + OFF_A + lr * 128 + ((((lane & 1) * 4) ^ (lr & 7)) << 4);
#pragma unroll 1
        for (int k = 0; k < 9; k++) {
          if (k == 3) {
            mbar_wait(BAR(BAR_SENT), layer);
            if (lane == 0) { cnt_arrive(CNT_X + (layer * 2 * 16 + r) * 9 + 7); }
            __syncwarp();
          }
          if (k == 3) {
            if (layer == 0) cnt_wait(CNT_CS, ep1 * NHELP);
            float4 cs[5];
#pragma unroll
            for (int i = 0; i < 5; i++) cs[i] = __ldcg(reinterpret_cast<const float4*>(g_cs1 + p * 576) + min(lane + i * 32, 143));
#pragma unroll
            for (int i = 0; i < 5; i++) reinterpret_cast<float4*>(smem + OFF_CS1)[min(lane + i * 32, 143) + min(lane + i * 32, 143) / 36] = cs[i];
            __syncwarp();
            mbar_arrive_if(BAR(BAR_CSOK), lane == 0);
          }
          mbar_wait(BAR(BAR_X1F + k), layer);
          uint4 v[4];
#pragma unroll
          for (int i = 0; i < 4; i++) v[i] = lds128((src ^ (i << 4)) + k * A_SLOT);
          sum8(v[0], s0, q0); sum8(v[1], s1, q1); sum8(v[2], s0, q0); sum8(v[3], s1, q1);
        }
        s0 += s1; q0 += q1;
        s0 += __shfl_xor_sync(0xffffffffu, s0, 1);
        q0 += __shfl_xor_sync(0xffffffffu, q0, 1);
        mbar_arrive_if(BAR(BAR_XRD), lane == 0);
        if (!(lane & 1)) stat_publish(&g_stat[(layer + 1) * SEQ + myrow], s0, q0, ep1);
        __syncwarp();
        stat_gather(&g_stat[(layer + 1) * SEQ + r * 128 + lane], ep1, reinterpret_cast<float*>(smem + OFF_RS) + frag_pos(lane), nullptr,
                    reinterpret_cast<float*>(smem + OFF_RS2) + ((lane >> 1) & 3) * 36 + (lane >> 3) * 2 + (lane & 1));
        __syncwarp();
        mbar_arrive_if(BAR(BAR_RSOK), lane == 0);
        if (layer == 0) {
          t0 = clock32();
#pragma unroll 1
          for (int i = 0; i < 32; i++) {
            pace(t0, i * CPF2_DT);
            asm volatile("prefetch.global.L2::evict_normal [%0];" ::"l"(cbase + (size_t)(i & 7) * 16 * SEQ * 2 + (i >> 3) * 256));
          }
        }
      }
    }
  } else {
    asm volatile("setmaxnreg.inc.sync.aligned.u32 232;");
    const uint32_t elect = (tid & 127) == 0;
    const uint32_t lane0 = lane == 0;
    if (wg == 1) {
      const int t = tid & 127;
      const int myrow = r * 128 + p * 16 + (t >> 3);
      const uint4* src = reinterpret_cast<const uint4*>(xin + (size_t)myrow * DM) + (t & 7);
      uint4* dst = reinterpret_cast<uint4*>(xout + (size_t)myrow * DM) + (t & 7);
      const int n = r * 9 + min(t >> 3, 8);
      const uint4* dsrc = reinterpret_cast<const uint4*>((m ? dim : dre) + (size_t)((n / 48) * 192 + q * 48 + n % 48) * DM) + (t & 7);
      float s = 0.f, qq = 0.f, sd = 0.f, s2 = 0.f, q2 = 0.f;
      uint4 v[3], d[3], vn[6], dn[6];
#pragma unroll
      for (int i = 0; i < 3; i++) { v[i] = __ldg(src + i * 8); d[i] = __ldg(dsrc + i * 8); }
#pragma unroll
      for (int i = 0; i < 6; i++) { vn[i] = __ldg(src + 24 + i * 8); dn[i] = __ldg(dsrc + 24 + i * 8); }
      START_SYNC();
#pragma unroll 1
      for (int it = 0; it < 72; it += 24) {
        sum8(v[0], s, qq); sum8(v[1], s2, q2); sum8(v[2], s, qq);
#pragma unroll
        for (int i = 0; i < 3; i++) {
          sd += ((bf_lo(d[i].x) + bf_hi(d[i].x)) + (bf_lo(d[i].y) + bf_hi(d[i].y))) + ((bf_lo(d[i].z) + bf_hi(d[i].z)) + (bf_lo(d[i].w) + bf_hi(d[i].w)));
          dst[it + i * 8] = v[i];
          v[i] = vn[i]; d[i] = dn[i]; vn[i] = vn[i + 3]; dn[i] = dn[i + 3];
        }
      }
      s += s2; qq += q2;
#pragma unroll
      for (int o = 1; o < 8; o <<= 1) {
        s += __shfl_xor_sync(0xffffffffu, s, o);
        qq += __shfl_xor_sync(0xffffffffu, qq, o);
        sd += __shfl_xor_sync(0xffffffffu, sd, o);
      }
      mbar_wait(BAR(BAR_EPOCH), 0);
      const uint32_t ep1 = *reinterpret_cast<volatile uint32_t*>(smem + OFF_EPOCH);
      if ((t & 7) == 0) {
        stat_publish(&g_stat[myrow], s, qq, ep1);
        if (t < 72) asm volatile("st.relaxed.gpu.global.u64 [%0], %1;" ::"l"(&g_csd[p * 144 + n]), "l"(((unsigned long long)ep1 << 32) | __float_as_uint(sd)) : "memory");
      }
      if (t < 32) g_rsum[(t >> 4) * SEQ + r * 128 + p * 16 + (t & 15)] = 0.f;
      __syncwarp();
      if (lane == 0) cnt_arrive(CNT_XINIT + r);
      asm volatile("bar.sync 2, 128;" ::: "memory");
    }

    const int srow = (lane & 7) + ((lane >> 3) & 1) * 8;
    const int schunk = lane >> 4;
    const int frow = warp * 16 + (lane >> 2);
    const uint32_t fpos = (warp * 8 + (lane >> 2)) * 16;
    const uint32_t bfull = BAR(BAR_BFULL);
    const uint32_t bempty = map_rank(BAR(BAR_BEMPTY), lane & 1);
    const uint32_t elect2 = (tid & 127) < 2;
    constexpr uint32_t alo0 = ((sbd + OFF_A) >> 4) | (1u << 16);

#pragma unroll 1
    for (int layer = 0; layer < 2; layer++) {
      float4 rsf = make_float4(0.f, 0.f, 0.f, 0.f);
      auto rowsums = [&](float (&rsum)[4]) {
#pragma unroll
        for (int i = 0; i < 4; i++) {
          rsum[i] += __shfl_xor_sync(0xffffffffu, rsum[i], 1);
          rsum[i] += __shfl_xor_sync(0xffffffffu, rsum[i], 2);
        }
        const int i = lane & 3;
        const float v = i == 0 ? rsum[0] : (i == 1 ? rsum[1] : (i == 2 ? rsum[2] : rsum[3]));
        asm volatile("red.global.add.f32 [%0], %1;" ::"l"(&g_rsum[layer * SEQ + r * 128 + warp * 32 + lane]), "f"(v) : "memory");
      };
      auto flush = [&](auto& acc0, auto& acc1, auto na, int pi, int atom0) {
        constexpr int NA = decltype(na)::value;
        const int ffn = pi >= 7;
        const uint32_t fdone = BAR(BAR_FDONE + ffn * 9 + atom0);
        mbar_wait(BAR(BAR_FOK + ffn), layer);
        if (atom0) mbar_wait(fdone - 8, layer);
        else if (NA == 3) mbar_wait(BAR(BAR_A8), layer);
        const uint32_t stg = sb + (NA == 3 ? OFF_A + 8 * A_SLOT : OFF_STG) + warp * 4096;
        const uint32_t sad = stg + srow * 128;
        const uint32_t dt = NA == 3 ? (pi == 1 ? FLUSH_DT_A : FLUSH_DT) : (pi == 10 ? FLUSH_DT_D : (pi == 9 ? FLUSH_DT_E : FLUSH_DT4));
        float rs[4];
        if (NA == 3) {
#pragma unroll
          for (int i = 0; i < 4; i++) rs[i] = 0.f;
        } else {
          rs[0] = rsf.x; rs[1] = rsf.y; rs[2] = rsf.z; rs[3] = rsf.w;
        }
        uint32_t tn = clock32() + warp * (dt / 4);
#pragma unroll
        for (int n = 0; n < 2 * NA; n++) {
          uint32_t w[16];
#pragma unroll
          for (int j = 0; j < 16; j++) {
            const int o = (n >> 1) * 32 + j * 2;
            if (NA == 3) {
              w[j] = (n & 1) ? pk(acc1[o], acc1[o + 1]) : pk(acc0[o], acc0[o + 1]);
              rs[(n & 1) * 2 + (j & 1)] += (n & 1) ? acc1[o] + acc1[o + 1] : acc0[o] + acc0[o + 1];
            } else {
              const float f = rs[(n & 1) * 2 + (j & 1)];
              w[j] = (n & 1) ? pk(acc1[o] * f, acc1[o + 1] * f) : pk(acc0[o] * f, acc0[o + 1] * f);
            }
          }
#pragma unroll
          for (int j = 0; j < 4; j++)
            stsm4(sad + (n & 1) * 2048 + (((j * 2 + schunk) ^ (srow & 7)) << 4), w[j * 4], w[j * 4 + 1], w[j * 4 + 2], w[j * 4 + 3]);
          if (NA == 3 && n == 5) rowsums(rs);
          fence_async_smem();
          if (n) tn += dt;
          spin_until(tn);
          __syncwarp();
          if (elect_one()) {
            tma_red2d(&maps.xred, stg + (n & 1) * 2048, (atom0 + (n >> 1)) * 64, r * 128 + (n & 1) * 64 + warp * 16);
            bulk_commit();
            if (n == 2 * NA - 1) {
              bulk_wait0();
              mbar_arrive(fdone + 8 * (NA - 1));
            } else if (n) {
              asm volatile("cp.async.bulk.wait_group 1;" ::: "memory");
              if (!(n & 1)) mbar_arrive(fdone + 8 * ((n >> 1) - 1));
            }
          }
          __syncwarp();
        }
      };
      if (wg == 0) {
        float acc0[72], acc1[72];
        if (layer == 0) { START_SYNC(); }
        constexpr uint32_t blo0 = ((sbd + OFF_B) >> 4) | (1u << 16);
        uint32_t ready = 0;
        auto step = [&](int s, auto first) {
          constexpr bool F = decltype(first)::value;
          if (!ready) {
            mbar_wait(BAR(BAR_XF + s), layer);
            mbar_wait(BAR(BAR_DF + s), layer);
            if (F && layer) mbar_wait(BAR(BAR_GO + 15), 0);
          }
          const uint32_t alo = alo0 + s * (A_SLOT >> 4);
          const uint32_t blo = blo0 + (s & 3) * (D_SLOT >> 4);
          wg_fence();
#pragma unroll
          for (int k = 0; k < 4; k++) {
            if (F && k == 0) {
              wgmma_n144<0, true>(acc0, desc(alo, DESC_HI_128), desc(blo, DESC_HI_128));
              wgmma_n144<0, true>(acc1, desc(alo + 512, DESC_HI_128), desc(blo, DESC_HI_128));
            } else {
              wgmma_n144<0, false>(acc0, desc(alo + k * 2, DESC_HI_128), desc(blo + k * 2, DESC_HI_128));
              wgmma_n144<0, false>(acc1, desc(alo + 512 + k * 2, DESC_HI_128), desc(blo + k * 2, DESC_HI_128));
            }
          }
          wg_commit();
          ready = mbar_test(BAR(BAR_XF + s + 1), layer) & mbar_test(BAR(BAR_DF + min(s + 1, 8)), layer);
          if (!F) {
            wg_wait<1>();
            mbar_arrive_cl_if(bempty + 8 * (BAR_DREL - BAR_BEMPTY - 1 + s), elect2);
            mbar_arrive_if(BAR(BAR_RG1 - 1 + s), elect);
          }
        };
        step(0, TrueT{});
#pragma unroll 1
        for (int s = 1; s < 9; s++) step(s, FalseT{});
        mbar_arrive_if(BAR(BAR_GO), elect);
        mbar_wait(BAR(BAR_CSD), 0);
        float2 cd[18];
#pragma unroll
        for (int i = 0; i < 9; i++) {
          const float4 t = lds128f(sb + OFF_CSD + (lane & 3) * 144 + i * 16);
          cd[i * 2] = make_float2(t.x, t.y); cd[i * 2 + 1] = make_float2(t.z, t.w);
        }
        mbar_wait(BAR(BAR_STAT), layer);
        const float sg = m ? -1.f : 1.f;
        float2 st[4];
        {
          const float4 a = lds128f(sb + OFF_RS + fpos), b = lds128f(sb + OFF_MEAN + fpos);
          st[0] = make_float2(a.x * sg, b.x); st[1] = make_float2(a.y * sg, b.y); st[2] = make_float2(a.z * sg, b.z); st[3] = make_float2(a.w * sg, b.w);
        }
        wg_wait<0>();
        reg_fence(acc0); reg_fence(acc1);
        auto val = [&](const float (&acc)[72], int b, int h, const float2& sv) {
          return pk(fmaf(cd[b].x, sv.y, acc[b * 4 + h * 2]) * sv.x, fmaf(cd[b].y, sv.y, acc[b * 4 + h * 2 + 1]) * sv.x);
        };
        {
          const bool odd = lane & 1;
          __nv_bfloat16* gp = g_ab + (size_t)((layer * 2 + m) * SEQ + r * 128 + frow) * DM + q * 48 + (lane & 1) * 8 + (lane & 2) * 2;
#pragma unroll
          for (int i = 0; i < 4; i++) {
#pragma unroll
            for (int b = 0; b < 6; b += 2) {
              const uint32_t va = val(i < 2 ? acc0 : acc1, b, i & 1, st[i]), vb = val(i < 2 ? acc0 : acc1, b + 1, i & 1, st[i]);
              const uint32_t o = __shfl_xor_sync(0xffffffffu, odd ? va : vb, 1);
              asm volatile("st.global.v2.u32 [%0], {%1, %2};" ::"l"(gp + ((i & 1) * 8 + (i >> 1) * 64) * DM + b * 8), "r"(odd ? o : va), "r"(odd ? vb : o) : "memory");
            }
          }
          mbar_arrive_if(BAR(BAR_RG1 + 8), elect);
#pragma unroll
          for (int i = 0; i < NB + 1; i++) mbar_arrive_cl_if(bempty + 8 * i, elect2 && i + layer < NB + 1);
          mbar_arrive_cl_if(bempty + 8 * (BAR_STG2 - BAR_BEMPTY), elect2);
          __syncwarp();
          if (lane0) cnt_arrive(CNT_AB + ((layer * 2 + m) * 16 + r) * 3);
        }
        asm volatile("bar.sync %0, 128;" ::"r"(1 + wg) : "memory");
        const uint32_t stg = sb + OFF_A + 6 * A_SLOT + (warp * 16 + srow) * 96 + schunk * 16;
#pragma unroll
        for (int b2 = 3; b2 < 9; b2++) {
          const uint32_t ad = stg + (b2 / 3) * A_SLOT + (b2 % 3) * 32;
          stsm4(ad, val(acc0, b2 * 2, 0, st[0]), val(acc0, b2 * 2, 1, st[1]), val(acc0, b2 * 2 + 1, 0, st[0]), val(acc0, b2 * 2 + 1, 1, st[1]));
          stsm4(ad + 64 * 96, val(acc1, b2 * 2, 0, st[2]), val(acc1, b2 * 2, 1, st[3]), val(acc1, b2 * 2 + 1, 0, st[2]), val(acc1, b2 * 2 + 1, 1, st[3]));
        }
        fence_async_smem();
        __syncwarp();
        mbar_arrive_if(BAR(BAR_ABSTG), lane0);
      }
#pragma unroll 1
      for (int pi = 2 - wg; pi < 7; pi += 2) {
        {
          float acc0[96], acc1[96];
          int atom0;
          int seq, nt, nt2 = 0, nt3 = 0, gap = 0, gap2 = 0, fbar, rbar = BAR_RNONE, sgm = pi;
          if (pi < 4) { atom0 = (pi - 1) * 3; nt = 8; seq = pi * 16 - 16; fbar = BAR_CF; if (pi == 3) rbar = BAR_RG2; }
          else if (pi == 4) { atom0 = 0; seq = 48; nt = G3A_C1 / 2; nt2 = (G3A_C2 - G3A_C1) / 2; nt3 = 9 - G3A_C2 / 2; gap = G3B_C1; gap2 = G3B_C2 - G3B_C1; fbar = BAR_X1F; }
          else if (pi == 5) { atom0 = 3; seq = 48 + G3A_C1; nt = G3B_C1 / 2; nt2 = (G3B_C2 - G3B_C1) / 2; nt3 = 9 - G3B_C2 / 2; gap = G3A_C2 - G3A_C1; gap2 = 18 - G3A_C2; fbar = BAR_X1F; rbar = BAR_RG3B; }
          else { atom0 = 6; seq = 84; nt = 9; fbar = BAR_X1F + 3; rbar = BAR_RG3C; sgm = 10; }
          constexpr uint32_t blo0 = ((sbd + OFF_B) >> 4) | ((4096u >> 4) << 16);
          uint32_t so = (seq % (NB + 1)) * 8, ph = seq / (NB + 1) + 1 - layer;
          uint32_t alo = alo0 + ((pi == 6) ? 6 * (A_SLOT >> 4) : 0);
          uint32_t fa = BAR(fbar), ra = BAR(rbar), go = BAR(BAR_GO + sgm);
          uint32_t pso, rel, epok = 0;
          auto issue = [&](uint32_t a, auto first) {
            constexpr bool F = decltype(first)::value;
            const uint32_t blo = blo0 + so * (B_SLOT >> 7);
            wg_fence();
            wgmma_n192<1, F>(acc0, desc(a, DESC_HI_128), desc(blo, DESC_HI_128));
            wgmma_n192<1, F>(acc1, desc(a + 512, DESC_HI_128), desc(blo, DESC_HI_128));
            wgmma_n192<1, false>(acc0, desc(a + 2, DESC_HI_128), desc(blo + 128, DESC_HI_128));
            wgmma_n192<1, false>(acc1, desc(a + 514, DESC_HI_128), desc(blo + 128, DESC_HI_128));
            wg_commit();
          };
          auto advance = [&]() { so += 8; if (so == (NB + 1) * 8) { so = 0; ph++; } };
          auto enter = [&]() {
            const uint32_t t0 = mbar_test(fa, layer), t1 = mbar_test(go - 8, layer), t2 = mbar_test(bfull + so, ph);
            if (!(t0 & t1 & t2)) {
              mbar_wait(fa, layer);
              mbar_wait(go - 8, layer);
              mbar_wait(bfull + so, ph);
            }
          };
          enter();
          issue(alo, TrueT{});
          pso = so;
          advance();
          mbar_wait(bfull + so, ph);
#pragma unroll 1
          for (;;) {
            issue(alo + 4, FalseT{});
            const uint32_t cso = so;
            advance();
            alo += A_SLOT >> 4;
            if (alo == alo0 + 9 * (A_SLOT >> 4)) alo = alo0 + 3 * (A_SLOT >> 4);
            fa += 8;
            if (--nt == 0) {
              mbar_arrive_if(go, elect);
              wg_wait<1>();
              mbar_arrive_cl_if(bempty + pso, elect2);
              if (nt2 == 0 && pi >= 4) {
                const uint32_t t0 = mbar_test(BAR(BAR_STAT + 1), layer), t1 = mbar_test(BAR(BAR_CSOK), layer), t2 = mbar_test(BAR(BAR_RG3B + 2), layer);
                epok = t0 & t1 & t2;
              }
              wg_wait<0>();
              mbar_arrive_cl_if(bempty + cso, elect2);
              mbar_arrive_if(ra, elect);
              if (nt2 == 0) break;
              nt = nt2; nt2 = nt3; nt3 = 0;
              const uint32_t t = so + gap * 8;
              so = t % ((NB + 1) * 8); ph += t / ((NB + 1) * 8);
              gap = gap2;
              go += 16;
              rel = 0;
              enter();
            } else {
              const uint32_t ready = mbar_test(fa, layer) & mbar_test(bfull + so, ph);
              wg_wait<1>();
              mbar_arrive_cl_if(bempty + pso, elect2);
              rel = 1;
              if (!ready) {
                mbar_wait(fa, layer);
                mbar_wait(bfull + so, ph);
              }
            }
            issue(alo, FalseT{});
            pso = so;
            advance();
            const uint32_t ready = mbar_test(bfull + so, ph);
            wg_wait<1>();
            mbar_arrive_cl_if(bempty + cso, rel && elect2);
            mbar_arrive_if(ra, rel && elect);
            ra += 8;
            if (!ready) {
              mbar_wait(bfull + so, ph);
            }
          }
        wg_wait<0>();
        reg_fence(acc0); reg_fence(acc1);
        if (pi >= 4 && pi <= 6) {
          if (!epok) {
            mbar_wait(BAR(BAR_STAT + 1), layer);
            mbar_wait(BAR(BAR_CSOK), layer);
            mbar_wait(BAR(BAR_RG3B + 2), layer);
          }
          if (pi == 5) mbar_wait(BAR(BAR_XRD), layer);
          if (pi == 6) asm volatile("bar.sync %0, 128;" ::"r"(1 + wg) : "memory");
          float2 st[4];
          {
            const float4 b = lds128f(sb + OFF_MEAN + fpos);
            st[0].y = b.x; st[1].y = b.y; st[2].y = b.z; st[3].y = b.w;
          }
          const uint32_t cs = sb + OFF_CS1 + (lane & 3) * 592 + atom0 * 64;
          const uint32_t dst = sb + OFF_A + atom0 * A_SLOT + (warp * 16 + srow) * 128;
          float4 cn[2];
          cn[0] = lds128f(cs); cn[1] = lds128f(cs + 16);
#pragma unroll
          for (int b2 = 0; b2 < 12; b2++) {
            if ((b2 & 3) == 0 && pi == 5) mbar_wait(BAR(BAR_RG3C + 3 + (b2 >> 2)), layer);
            const float2 c0 = make_float2(cn[b2 & 1].x, cn[b2 & 1].y), c1 = make_float2(cn[b2 & 1].z, cn[b2 & 1].w);
            if (b2 + 2 < 12) cn[b2 & 1] = lds128f(cs + (b2 + 2) * 16);
            const uint32_t ad = dst + (b2 >> 2) * A_SLOT + ((((b2 & 3) * 2 + schunk) ^ (srow & 7)) << 4);
            const int o = b2 * 8;
            stsm4(ad,
                  pk_relu(fmaf(c0.x, st[0].y, acc0[o]), fmaf(c0.y, st[0].y, acc0[o + 1])),
                  pk_relu(fmaf(c0.x, st[1].y, acc0[o + 2]), fmaf(c0.y, st[1].y, acc0[o + 3])),
                  pk_relu(fmaf(c1.x, st[0].y, acc0[o + 4]), fmaf(c1.y, st[0].y, acc0[o + 5])),
                  pk_relu(fmaf(c1.x, st[1].y, acc0[o + 6]), fmaf(c1.y, st[1].y, acc0[o + 7])));
            stsm4(ad + 8192,
                  pk_relu(fmaf(c0.x, st[2].y, acc1[o]), fmaf(c0.y, st[2].y, acc1[o + 1])),
                  pk_relu(fmaf(c0.x, st[3].y, acc1[o + 2]), fmaf(c0.y, st[3].y, acc1[o + 3])),
                  pk_relu(fmaf(c1.x, st[2].y, acc1[o + 4]), fmaf(c1.y, st[2].y, acc1[o + 5])),
                  pk_relu(fmaf(c1.x, st[3].y, acc1[o + 6]), fmaf(c1.y, st[3].y, acc1[o + 7])));
            if ((b2 & 3) == 3 && (pi == 6 || b2 == 11)) {
              fence_async_smem();
              __syncwarp();
              mbar_arrive_if(BAR(BAR_HF + atom0 + (b2 >> 2)), lane0);
              if (b2 == 11 && pi != 6) { mbar_arrive_if(BAR(BAR_HF + atom0), lane0); mbar_arrive_if(BAR(BAR_HF + atom0 + 1), lane0); }
            }
          }
        } else if (pi == 3) {
          asm volatile("bar.sync %0, 128;" ::"r"(1 + wg) : "memory");
          const uint32_t dst = sb + OFF_A + 6 * A_SLOT + (warp * 16 + srow) * 128;
          float rs[4] = {0.f, 0.f, 0.f, 0.f};
#pragma unroll
          for (int b2 = 0; b2 < 12; b2++) {
            if (b2 == 8) mbar_wait(BAR(BAR_FDONE + 5), layer);
            const uint32_t ad = dst + (b2 >> 2) * A_SLOT + ((((b2 & 3) * 2 + schunk) ^ (srow & 7)) << 4);
            const int o = b2 * 8;
            stsm4(ad, pk(acc0[o], acc0[o + 1]), pk(acc0[o + 2], acc0[o + 3]), pk(acc0[o + 4], acc0[o + 5]), pk(acc0[o + 6], acc0[o + 7]));
            stsm4(ad + 8192, pk(acc1[o], acc1[o + 1]), pk(acc1[o + 2], acc1[o + 3]), pk(acc1[o + 4], acc1[o + 5]), pk(acc1[o + 6], acc1[o + 7]));
            rs[0] += (acc0[o] + acc0[o + 1]) + (acc0[o + 4] + acc0[o + 5]);
            rs[1] += (acc0[o + 2] + acc0[o + 3]) + (acc0[o + 6] + acc0[o + 7]);
            rs[2] += (acc1[o] + acc1[o + 1]) + (acc1[o + 4] + acc1[o + 5]);
            rs[3] += (acc1[o + 2] + acc1[o + 3]) + (acc1[o + 6] + acc1[o + 7]);
            if ((b2 & 3) == 3) {
              fence_async_smem();
              __syncwarp();
              if (b2 == 3) {
                if (lane0) {
                  tma_red2d(&maps.xred, sb + OFF_A + 6 * A_SLOT + warp * 2048, 384, r * 128 + warp * 16);
                  tma_red2d(&maps.xred, sb + OFF_A + 6 * A_SLOT + 8192 + warp * 2048, 384, r * 128 + 64 + warp * 16);
                  bulk_commit();
                }
              } else {
                mbar_arrive_if(BAR(BAR_FDONE + 6 + (b2 >> 2)), lane0);
              }
            }
          }
          rowsums(rs);
          bulk_wait0();
          __syncwarp();
          mbar_arrive_if(BAR(BAR_FDONE + 6), lane0);
        } else {
          flush(acc0, acc1, IntT<3>{}, pi, atom0);
        }
        }
      }
      float2 rsv[16];
      mbar_wait(BAR(BAR_RSOK), layer);
      rsf = lds128f(sb + OFF_RS + fpos);
      if (wg) {
#pragma unroll
        for (int i = 0; i < 8; i++) {
          const uint4 t = lds128(sb + OFF_RS2 + (lane & 3) * 144 + i * 16);
          rsv[i * 2] = make_float2(__uint_as_float(t.x), __uint_as_float(t.y));
          rsv[i * 2 + 1] = make_float2(__uint_as_float(t.z), __uint_as_float(t.w));
        }
      } else {
#pragma unroll
        for (int i = 0; i < 16; i++) rsv[i] = make_float2(0.f, 0.f);
      }
#pragma unroll 1
      for (int pi = 8 - wg; pi < 12; pi += 2) {
        {
          const int seq = (pi - 7) * 12;
          uint32_t so = (seq % NB) * 8, ph = seq / NB + layer, pso = 0, cso;
          const uint32_t go = BAR(BAR_GO + 4 + pi);
          auto enter = [&]() {
            const uint32_t t0 = mbar_test(BAR(BAR_HF), layer), t1 = mbar_test(go - 8, layer), t2 = mbar_test(bfull + so, ph);
            if (!(t0 & t1 & t2)) {
              mbar_wait(BAR(BAR_HF), layer);
              mbar_wait(go - 8, layer);
              mbar_wait(bfull + so, ph);
            }
          };
          auto advance = [&]() { cso = so; so += 8; if (so == NB * 8) { so = 0; ph++; } };
          if (pi < 11) {
            float a0[64], a1[64];
            constexpr uint32_t blo0 = ((sbd + OFF_B) >> 4) | ((6144u >> 4) << 16);
            uint32_t alo = alo0, hf = BAR(BAR_HF);
            auto issue = [&](auto jj, auto first) {
              constexpr int J = decltype(jj)::value;
              constexpr bool F = decltype(first)::value;
              const uint32_t blo = blo0 + so * (B_SLOT >> 7);
              wg_fence();
#pragma unroll
              for (int j = 0; j < 3; j++) {
                const int u = J * 3 + j;
                const uint64_t da0 = desc(alo + (u >> 2) * (A_SLOT >> 4) + (u & 3) * 2, DESC_HI_128);
                const uint64_t da1 = desc(alo + (u >> 2) * (A_SLOT >> 4) + (u & 3) * 2 + 512, DESC_HI_128);
                const uint64_t db = desc(blo + j * 128, DESC_HI_128);
                if (F && j == 0) { wgmma_n128<1, true>(a0, da0, db); wgmma_n128<1, true>(a1, da1, db); }
                else { wgmma_n128<1, false>(a0, da0, db); wgmma_n128<1, false>(a1, da1, db); }
              }
              wg_commit();
              advance();
            };
            auto next = [&](int tile, auto first) {
              uint32_t ready = mbar_test(bfull + so, ph);
              if (tile >= 0) ready &= mbar_test(hf + 8 * tile, layer);
              if (!decltype(first)::value) {
                wg_wait<1>();
                mbar_arrive_cl_if(bempty + pso, elect2);
              }
              pso = cso;
              if (!ready) {
                if (tile >= 0) mbar_wait(hf + 8 * tile, layer);
                mbar_wait(bfull + so, ph);
              }
            };
            enter();
            issue(IntT<0>{}, TrueT{});
            next(1, TrueT{});
#pragma unroll 1
            for (;;) {
              issue(IntT<1>{}, FalseT{});
              next(2, FalseT{});
              issue(IntT<2>{}, FalseT{});
              next(-1, FalseT{});
              issue(IntT<3>{}, FalseT{});
              if (alo == alo0 + 6 * (A_SLOT >> 4)) break;
              alo += 3 * (A_SLOT >> 4);
              hf += 24;
              next(0, FalseT{});
              issue(IntT<0>{}, FalseT{});
              next(1, FalseT{});
            }
            mbar_arrive_if(go, elect);
            wg_wait<1>();
            mbar_arrive_cl_if(bempty + pso, elect2);
            wg_wait<0>();
            mbar_arrive_cl_if(bempty + cso, elect2);
            reg_fence(a0); reg_fence(a1);
            flush(a0, a1, IntT<2>{}, pi, (pi - 7) * 2);
          } else {
            float a0[64];
            auto step = [&](int s, auto first) {
              constexpr bool F = decltype(first)::value;
              const uint32_t blo = (((sbd + OFF_B) >> 4) | (1u << 16)) + so * (B_SLOT >> 7);
              wg_fence();
#pragma unroll
              for (int j = 0; j < 6; j++) {
                const int u = s * 6 + j;
                const uint64_t dh = desc(alo0 + (u >> 2) * (A_SLOT >> 4) + (u & 3) * 2, DESC_HI_128);
                if (F && j == 0) wgmma_n128<0, true, 1>(a0, desc(blo, DESC_HI_128), dh);
                else wgmma_n128<0, false, 1>(a0, desc(blo + j * 128, DESC_HI_128), dh);
              }
              wg_commit();
              advance();
              mbar_arrive_if(go, elect && s == 5);
              const uint32_t ready = mbar_test(bfull + so, ph) | (s == 5);
              if (!F) {
                wg_wait<1>();
                mbar_arrive_cl_if(bempty + pso, elect2);
                mbar_arrive_if(BAR(BAR_RG4 - 1 + ((6 * s) >> 2)), elect);
                mbar_arrive_if(BAR(BAR_RG4 - 2 + ((6 * s) >> 2)), elect && !(s & 1));
              }
              pso = cso;
              if (!ready) mbar_wait(bfull + so, ph);
            };
            enter();
            step(0, TrueT{});
#pragma unroll 1
            for (int s = 1; s < 6; s++) step(s, FalseT{});
            wg_wait<0>();
            mbar_arrive_cl_if(bempty + pso, elect2);
            mbar_arrive_if(BAR(BAR_RG4 + 7), elect);
            mbar_arrive_if(BAR(BAR_RG4 + 8), elect);
            reg_fence(a0);
            {
              asm volatile("bar.sync %0, 128;" ::"r"(1 + wg) : "memory");
              const uint32_t tb = sb + OFF_A + 8 * A_SLOT;
              const uint32_t ad = tb + ((lane >> 4) * 8 + (lane & 7)) * 128 + (((warp * 2 + ((lane >> 3) & 1)) ^ (lane & 7)) << 4);
#pragma unroll
              for (int b2 = 0; b2 < 8; b2++) {
                const float2 f0 = rsv[b2 * 2], f1 = rsv[b2 * 2 + 1];
                const int o = b2 * 8;
                asm volatile("stmatrix.sync.aligned.m8n8.x4.trans.shared.b16 [%0], {%1,%2,%3,%4};" ::"r"(ad + b2 * 2048),
                             "r"(pk(a0[o] * f0.x, a0[o + 1] * f0.y)), "r"(pk(a0[o + 2] * f0.x, a0[o + 3] * f0.y)),
                             "r"(pk(a0[o + 4] * f1.x, a0[o + 5] * f1.y)), "r"(pk(a0[o + 6] * f1.x, a0[o + 7] * f1.y)));
              }
              fence_async_smem();
              __syncwarp();
              mbar_arrive_if(BAR(BAR_FDONE + 17), lane0);
              if (layer == 0) {
                const int row = tid & 127;
                const uint32_t ra = sb + OFF_A + row * 128 + ((row & 15) << 3);
                float s0 = 0.f, q0 = 0.f, s1 = 0.f, q1 = 0.f;
#pragma unroll 1
                for (int k = 0; k < 9; k++) {
                  mbar_wait(BAR(BAR_XF + k), 1);
                  uint4 v[8];
#pragma unroll
                  for (int i = 0; i < 8; i++) {
                    asm volatile("ld.shared.v2.u32 {%0,%1}, [%2];" : "=r"(v[i].x), "=r"(v[i].y) : "r"((ra ^ (i << 4)) + k * A_SLOT) : "memory");
                    asm volatile("ld.shared.v2.u32 {%0,%1}, [%2];" : "=r"(v[i].z), "=r"(v[i].w) : "r"((ra ^ ((i << 4) | 8)) + k * A_SLOT) : "memory");
                  }
#pragma unroll
                  for (int i = 0; i < 8; i += 2) { sum8(v[i], s0, q0); sum8(v[i + 1], s1, q1); }
                  if (k < CE1) {
                    asm volatile("bar.sync %0, 128;" ::"r"(1 + wg) : "memory");
                    mbar_arrive_if(BAR(BAR_RD + k), elect);
                  }
                }
                const float mean = (s0 + s1) * (1.0f / DM);
                reinterpret_cast<float*>(smem + OFF_RS)[frag_pos(row)] = rsqrtf(fmaxf((q0 + q1) * (1.0f / DM) - mean * mean, 0.f) + 1e-5f);
                reinterpret_cast<float*>(smem + OFF_MEAN)[frag_pos(row)] = -mean;
                asm volatile("bar.sync %0, 128;" ::"r"(1 + wg) : "memory");
                mbar_arrive_if(BAR(BAR_STAT), elect);
              }
            }
          }
        }
      }
    }
  }
#undef BAR
}

typedef CUresult (*EncodeFn)(CUtensorMap*, CUtensorMapDataType, cuuint32_t, void*, const cuuint64_t*, const cuuint64_t*, const cuuint32_t*,
                             const cuuint32_t*, CUtensorMapInterleave, CUtensorMapSwizzle, CUtensorMapL2promotion, CUtensorMapFloatOOBfill);

void make2d(EncodeFn enc, CUtensorMap* m, const void* ptr, uint64_t inner, uint64_t outer, uint32_t bi, uint32_t bo, CUtensorMapSwizzle sw) {
  cuuint64_t d[2] = {inner, outer};
  cuuint64_t s[1] = {inner * 2};
  cuuint32_t b[2] = {bi, bo}, e[2] = {1, 1};
  enc(m, CU_TENSOR_MAP_DATA_TYPE_BFLOAT16, 2, const_cast<void*>(ptr), d, s, b, e, CU_TENSOR_MAP_INTERLEAVE_NONE, sw,
      CU_TENSOR_MAP_L2_PROMOTION_L2_128B, CU_TENSOR_MAP_FLOAT_OOB_FILL_NONE);
}
void make3d(EncodeFn enc, CUtensorMap* m, const void* ptr, uint64_t d0, uint64_t d1, uint64_t d2, uint64_t s1, uint64_t s2,
            uint32_t b0, uint32_t b1, uint32_t b2, CUtensorMapSwizzle sw) {
  cuuint64_t d[3] = {d0, d1, d2};
  cuuint64_t s[2] = {s1, s2};
  cuuint32_t b[3] = {b0, b1, b2}, e[3] = {1, 1, 1};
  enc(m, CU_TENSOR_MAP_DATA_TYPE_BFLOAT16, 3, const_cast<void*>(ptr), d, s, b, e, CU_TENSOR_MAP_INTERLEAVE_NONE, sw,
      CU_TENSOR_MAP_L2_PROMOTION_L2_128B, CU_TENSOR_MAP_FLOAT_OOB_FILL_NONE);
}

}

extern "C" void kernel_launch(void* const* d_in, const int* in_sizes, int n_in, void* d_out, int out_size) {
  (void)in_sizes; (void)n_in; (void)out_size;
  const __nv_bfloat16* x = (const __nv_bfloat16*)d_in[0];
  const __nv_bfloat16* cr = (const __nv_bfloat16*)d_in[1];
  const __nv_bfloat16* ci = (const __nv_bfloat16*)d_in[2];
  const __nv_bfloat16* dr = (const __nv_bfloat16*)d_in[3];
  const __nv_bfloat16* di = (const __nv_bfloat16*)d_in[4];
  const __nv_bfloat16* w1 = (const __nv_bfloat16*)d_in[6];
  const __nv_bfloat16* w2 = (const __nv_bfloat16*)d_in[7];
  __nv_bfloat16* out = (__nv_bfloat16*)d_out;

  void* fn = nullptr;
  cudaDriverEntryPointQueryResult qr;
  cudaGetDriverEntryPoint("cuTensorMapEncodeTiled", &fn, cudaEnableDefault, &qr);
  EncodeFn enc = (EncodeFn)fn;
  void* ab = nullptr;
  cudaGetSymbolAddress(&ab, g_ab);

  Maps maps;
  make2d(enc, &maps.xin, x, DM, SEQ, 64, 128, CU_TENSOR_MAP_SWIZZLE_128B);
  make2d(enc, &maps.xld, out, DM, SEQ, 64, 128, CU_TENSOR_MAP_SWIZZLE_128B);
  make2d(enc, &maps.xred, out, DM, SEQ, 64, 16, CU_TENSOR_MAP_SWIZZLE_128B);
  make2d(enc, &maps.cr, cr, SEQ, SEQ, 64, 128, CU_TENSOR_MAP_SWIZZLE_128B);
  make2d(enc, &maps.ci, ci, SEQ, SEQ, 64, 128, CU_TENSOR_MAP_SWIZZLE_128B);
  make3d(enc, &maps.dr, dr, DM, 192, 3, DM * 2, 192 * DM * 2, 64, 48, 3, CU_TENSOR_MAP_SWIZZLE_128B);
  make3d(enc, &maps.di, di, DM, 192, 3, DM * 2, 192 * DM * 2, 64, 48, 3, CU_TENSOR_MAP_SWIZZLE_128B);
  make3d(enc, &maps.abld, ab, 64, 4 * SEQ, DM / 64, DM * 2, 128, 64, 32, 3, CU_TENSOR_MAP_SWIZZLE_128B);
  make2d(enc, &maps.abst, ab, DM, 4 * SEQ, 48, 128, CU_TENSOR_MAP_SWIZZLE_NONE);
  make3d(enc, &maps.w1, w1, 64, DM, DFF / 64, DFF * 2, 128, 64, 32, 3, CU_TENSOR_MAP_SWIZZLE_128B);
  make3d(enc, &maps.w2, w2, 64, DFF, DM / 64, DM * 2, 128, 64, 48, 2, CU_TENSOR_MAP_SWIZZLE_128B);
  make3d(enc, &maps.w2n, w2, 64, DFF, DM / 64, DM * 2, 128, 64, 96, 1, CU_TENSOR_MAP_SWIZZLE_128B);

  cudaFuncSetAttribute(fnet_ffn_kernel, cudaFuncAttributeMaxDynamicSharedMemorySize, SMEM_BYTES);
  cudaLaunchConfig_t cfg = {};
  cfg.gridDim = dim3(NGRID);
  cfg.blockDim = dim3(384);
  cfg.dynamicSmemBytes = SMEM_BYTES;
  cfg.stream = cudaStreamPerThread;
  cudaLaunchAttribute at[1];
  at[0].id = cudaLaunchAttributeClusterDimension;
  at[0].val.clusterDim.x = 2; at[0].val.clusterDim.y = 1; at[0].val.clusterDim.z = 1;
  cfg.attrs = at;
  cfg.numAttrs = 1;
  cudaLaunchKernelEx(&cfg, fnet_ffn_kernel, maps, x, cr, ci, dr, di, w2, out);
}
```

```cpp
#include <cuda_runtime.h>
#include <cuda_bf16.h>
#include <cuda.h>
#include <stdint.h>

namespace {

constexpr int SEQ = 2048, DM = 576, DFF = 4608;
constexpr int NHELP = 4, NWORK = 128, NGRID = NHELP + NWORK;

constexpr int A_SLOT = 16384, B_SLOT = 12288, NB = 5, D_SLOT = 18432;
constexpr int OFF_A = 0;
constexpr int OFF_B = 9 * A_SLOT;
constexpr int OFF_STG = OFF_B + NB * B_SLOT;
constexpr int OFF_CS1 = OFF_STG + 12288;
constexpr int OFF_CSD = OFF_STG + 16384;
constexpr int OFF_EPOCH = OFF_CSD + 576;
constexpr int OFF_RS = OFF_CSD + 640;
constexpr int OFF_BAR = OFF_RS + 512;
constexpr int SMEM_BYTES = 232448;

constexpr int BAR_HF = 0  , BAR_ABSTG = 9, BAR_FDONE = 11  , BAR_ABH = 29  ,
              BAR_BEMPTY = 32  , BAR_DREL = 38  , BAR_STGF = 46, BAR_STG2 = 47,
              BAR_CF = 48  , BAR_X1F = 56  ,
              BAR_RG1 = 68, BAR_RG2 = 77, BAR_RG3B = 86, BAR_RG3C = 95, BAR_RG4 = 104, BAR_RNONE = 113  ,
              BAR_STAT = 122  , BAR_FOK = 124  , BAR_EPOCH = 126, BAR_CSD = 127,
              BAR_XF = 128  , BAR_DF = 137  , BAR_GO = 146  , BAR_XOK = 162  , BAR_SENT = 168,
              BAR_RSOK = 169, BAR_CSOK = 170, BAR_A7 = 171, BAR_RD = 172  , BAR_BFULL = 177  , BAR_A8 = 183,
              BAR_AB1 = 184, BAR_XRD = 185, BAR_STATY = 186, BAR_XFY = 187  , BAR_SENTX = 190, BAR_SENTY = 191,
              BAR_ABOK = 192  , NBAR = 208;
constexpr int OFF_MEAN = OFF_BAR + NBAR * 8;
constexpr int OFF_RS2 = OFF_MEAN + 512;
static_assert(OFF_RS2 % 16 == 0 && OFF_RS2 + 576 <= SMEM_BYTES, "smem");

constexpr int CNT_STRIDE = 32;
constexpr int CNT_AB = 0;
constexpr int CNT_X = 256;
constexpr int CNT_XINIT = CNT_X + 432;
constexpr int CNT_G3 = CNT_XINIT + 16;
constexpr int CNT_CS = CNT_G3 + 32;
constexpr int CNT_TICKET = CNT_CS + 1;
constexpr int NCNT = CNT_TICKET + 1;

__device__ uint32_t g_cnt[NCNT * CNT_STRIDE];
__device__ __align__(128) __nv_bfloat16 g_ab[2 * 2 * SEQ * DM];
__device__ __align__(16) float g_cs1[DFF];
__device__ __align__(16) float g_rsum[2 * SEQ];
__device__ __align__(16) unsigned long long g_csd[8 * 144];
__device__ ulonglong2 g_stat[3 * SEQ];

template <int V> struct IntT { static constexpr int value = V; };
struct TrueT { static constexpr bool value = true; };
struct FalseT { static constexpr bool value = false; };

struct Maps {
  CUtensorMap xin, xld, xh, xred, cr, ci, dr, di, abld, abst, w1, w2, w2n;
};

template<int TB, bool FIRST, int TA = 0> __device__ __forceinline__ void wgmma_n128(float (&d)[64], uint64_t da, uint64_t db){
  if (FIRST) {
    asm volatile("wgmma.mma_async.sync.aligned.m64n128k16.f32.bf16.bf16 {%0, %1, %2, %3, %4, %5, %6, %7, %8, %9, %10, %11, %12, %13, %14, %15, %16, %17, %18, %19, %20, %21, %22, %23, %24, %25, %26, %27, %28, %29, %30, %31, %32, %33, %34, %35, %36, %37, %38, %39, %40, %41, %42, %43, %44, %45, %46, %47, %48, %49, %50, %51, %52, %53, %54, %55, %56, %57, %58, %59, %60, %61, %62, %63}, %64, %65, 0, 1, 1, %67, %66;"
     : "=f"(d[0]), "=f"(d[1]), "=f"(d[2]), "=f"(d[3]), "=f"(d[4]), "=f"(d[5]), "=f"(d[6]), "=f"(d[7]), "=f"(d[8]), "=f"(d[9]), "=f"(d[10]), "=f"(d[11]), "=f"(d[12]), "=f"(d[13]), "=f"(d[14]), "=f"(d[15]), "=f"(d[16]), "=f"(d[17]), "=f"(d[18]), "=f"(d[19]), "=f"(d[20]), "=f"(d[21]), "=f"(d[22]), "=f"(d[23]), "=f"(d[24]), "=f"(d[25]), "=f"(d[26]), "=f"(d[27]), "=f"(d[28]), "=f"(d[29]), "=f"(d[30]), "=f"(d[31]), "=f"(d[32]), "=f"(d[33]), "=f"(d[34]), "=f"(d[35]), "=f"(d[36]), "=f"(d[37]), "=f"(d[38]), "=f"(d[39]), "=f"(d[40]), "=f"(d[41]), "=f"(d[42]), "=f"(d[43]), "=f"(d[44]), "=f"(d[45]), "=f"(d[46]), "=f"(d[47]), "=f"(d[48]), "=f"(d[49]), "=f"(d[50]), "=f"(d[51]), "=f"(d[52]), "=f"(d[53]), "=f"(d[54]), "=f"(d[55]), "=f"(d[56]), "=f"(d[57]), "=f"(d[58]), "=f"(d[59]), "=f"(d[60]), "=f"(d[61]), "=f"(d[62]), "=f"(d[63])
     : "l"(da), "l"(db), "n"(TB), "n"(TA));
  } else {
    asm volatile("wgmma.mma_async.sync.aligned.m64n128k16.f32.bf16.bf16 {%0, %1, %2, %3, %4, %5, %6, %7, %8, %9, %10, %11, %12, %13, %14, %15, %16, %17, %18, %19, %20, %21, %22, %23, %24, %25, %26, %27, %28, %29, %30, %31, %32, %33, %34, %35, %36, %37, %38, %39, %40, %41, %42, %43, %44, %45, %46, %47, %48, %49, %50, %51, %52, %53, %54, %55, %56, %57, %58, %59, %60, %61, %62, %63}, %64, %65, 1, 1, 1, %67, %66;"
     : "+f"(d[0]), "+f"(d[1]), "+f"(d[2]), "+f"(d[3]), "+f"(d[4]), "+f"(d[5]), "+f"(d[6]), "+f"(d[7]), "+f"(d[8]), "+f"(d[9]), "+f"(d[10]), "+f"(d[11]), "+f"(d[12]), "+f"(d[13]), "+f"(d[14]), "+f"(d[15]), "+f"(d[16]), "+f"(d[17]), "+f"(d[18]), "+f"(d[19]), "+f"(d[20]), "+f"(d[21]), "+f"(d[22]), "+f"(d[23]), "+f"(d[24]), "+f"(d[25]), "+f"(d[26]), "+f"(d[27]), "+f"(d[28]), "+f"(d[29]), "+f"(d[30]), "+f"(d[31]), "+f"(d[32]), "+f"(d[33]), "+f"(d[34]), "+f"(d[35]), "+f"(d[36]), "+f"(d[37]), "+f"(d[38]), "+f"(d[39]), "+f"(d[40]), "+f"(d[41]), "+f"(d[42]), "+f"(d[43]), "+f"(d[44]), "+f"(d[45]), "+f"(d[46]), "+f"(d[47]), "+f"(d[48]), "+f"(d[49]), "+f"(d[50]), "+f"(d[51]), "+f"(d[52]), "+f"(d[53]), "+f"(d[54]), "+f"(d[55]), "+f"(d[56]), "+f"(d[57]), "+f"(d[58]), "+f"(d[59]), "+f"(d[60]), "+f"(d[61]), "+f"(d[62]), "+f"(d[63])
     : "l"(da), "l"(db), "n"(TB), "n"(TA));
  }
}
template<int TB, bool FIRST, int TA = 0> __device__ __forceinline__ void wgmma_n144(float (&d)[72], uint64_t da, uint64_t db){
  if (FIRST) {
    asm volatile("wgmma.mma_async.sync.aligned.m64n144k16.f32.bf16.bf16 {%0, %1, %2, %3, %4, %5, %6, %7, %8, %9, %10, %11, %12, %13, %14, %15, %16, %17, %18, %19, %20, %21, %22, %23, %24, %25, %26, %27, %28, %29, %30, %31, %32, %33, %34, %35, %36, %37, %38, %39, %40, %41, %42, %43, %44, %45, %46, %47, %48, %49, %50, %51, %52, %53, %54, %55, %56, %57, %58, %59, %60, %61, %62, %63, %64, %65, %66, %67, %68, %69, %70, %71}, %72, %73, 0, 1, 1, %75, %74;"
     : "=f"(d[0]), "=f"(d[1]), "=f"(d[2]), "=f"(d[3]), "=f"(d[4]), "=f"(d[5]), "=f"(d[6]), "=f"(d[7]), "=f"(d[8]), "=f"(d[9]), "=f"(d[10]), "=f"(d[11]), "=f"(d[12]), "=f"(d[13]), "=f"(d[14]), "=f"(d[15]), "=f"(d[16]), "=f"(d[17]), "=f"(d[18]), "=f"(d[19]), "=f"(d[20]), "=f"(d[21]), "=f"(d[22]), "=f"(d[23]), "=f"(d[24]), "=f"(d[25]), "=f"(d[26]), "=f"(d[27]), "=f"(d[28]), "=f"(d[29]), "=f"(d[30]), "=f"(d[31]), "=f"(d[32]), "=f"(d[33]), "=f"(d[34]), "=f"(d[35]), "=f"(d[36]), "=f"(d[37]), "=f"(d[38]), "=f"(d[39]), "=f"(d[40]), "=f"(d[41]), "=f"(d[42]), "=f"(d[43]), "=f"(d[44]), "=f"(d[45]), "=f"(d[46]), "=f"(d[47]), "=f"(d[48]), "=f"(d[49]), "=f"(d[50]), "=f"(d[51]), "=f"(d[52]), "=f"(d[53]), "=f"(d[54]), "=f"(d[55]), "=f"(d[56]), "=f"(d[57]), "=f"(d[58]), "=f"(d[59]), "=f"(d[60]), "=f"(d[61]), "=f"(d[62]), "=f"(d[63]), "=f"(d[64]), "=f"(d[65]), "=f"(d[66]), "=f"(d[67]), "=f"(d[68]), "=f"(d[69]), "=f"(d[70]), "=f"(d[71])
     : "l"(da), "l"(db), "n"(TB), "n"(TA));
  } else {
    asm volatile("wgmma.mma_async.sync.aligned.m64n144k16.f32.bf16.bf16 {%0, %1, %2, %3, %4, %5, %6, %7, %8, %9, %10, %11, %12, %13, %14, %15, %16, %17, %18, %19, %20, %21, %22, %23, %24, %25, %26, %27, %28, %29, %30, %31, %32, %33, %34, %35, %36, %37, %38, %39, %40, %41, %42, %43, %44, %45, %46, %47, %48, %49, %50, %51, %52, %53, %54, %55, %56, %57, %58, %59, %60, %61, %62, %63, %64, %65, %66, %67, %68, %69, %70, %71}, %72, %73, 1, 1, 1, %75, %74;"
     : "+f"(d[0]), "+f"(d[1]), "+f"(d[2]), "+f"(d[3]), "+f"(d[4]), "+f"(d[5]), "+f"(d[6]), "+f"(d[7]), "+f"(d[8]), "+f"(d[9]), "+f"(d[10]), "+f"(d[11]), "+f"(d[12]), "+f"(d[13]), "+f"(d[14]), "+f"(d[15]), "+f"(d[16]), "+f"(d[17]), "+f"(d[18]), "+f"(d[19]), "+f"(d[20]), "+f"(d[21]), "+f"(d[22]), "+f"(d[23]), "+f"(d[24]), "+f"(d[25]), "+f"(d[26]), "+f"(d[27]), "+f"(d[28]), "+f"(d[29]), "+f"(d[30]), "+f"(d[31]), "+f"(d[32]), "+f"(d[33]), "+f"(d[34]), "+f"(d[35]), "+f"(d[36]), "+f"(d[37]), "+f"(d[38]), "+f"(d[39]), "+f"(d[40]), "+f"(d[41]), "+f"(d[42]), "+f"(d[43]), "+f"(d[44]), "+f"(d[45]), "+f"(d[46]), "+f"(d[47]), "+f"(d[48]), "+f"(d[49]), "+f"(d[50]), "+f"(d[51]), "+f"(d[52]), "+f"(d[53]), "+f"(d[54]), "+f"(d[55]), "+f"(d[56]), "+f"(d[57]), "+f"(d[58]), "+f"(d[59]), "+f"(d[60]), "+f"(d[61]), "+f"(d[62]), "+f"(d[63]), "+f"(d[64]), "+f"(d[65]), "+f"(d[66]), "+f"(d[67]), "+f"(d[68]), "+f"(d[69]), "+f"(d[70]), "+f"(d[71])
     : "l"(da), "l"(db), "n"(TB), "n"(TA));
  }
}
template<int TB, bool FIRST, int TA = 0> __device__ __forceinline__ void wgmma_n192(float (&d)[96], uint64_t da, uint64_t db){
  if (FIRST) {
    asm volatile("wgmma.mma_async.sync.aligned.m64n192k16.f32.bf16.bf16 {%0, %1, %2, %3, %4, %5, %6, %7, %8, %9, %10, %11, %12, %13, %14, %15, %16, %17, %18, %19, %20, %21, %22, %23, %24, %25, %26, %27, %28, %29, %30, %31, %32, %33, %34, %35, %36, %37, %38, %39, %40, %41, %42, %43, %44, %45, %46, %47, %48, %49, %50, %51, %52, %53, %54, %55, %56, %57, %58, %59, %60, %61, %62, %63, %64, %65, %66, %67, %68, %69, %70, %71, %72, %73, %74, %75, %76, %77, %78, %79, %80, %81, %82, %83, %84, %85, %86, %87, %88, %89, %90, %91, %92, %93, %94, %95}, %96, %97, 0, 1, 1, %99, %98;"
     : "=f"(d[0]), "=f"(d[1]), "=f"(d[2]), "=f"(d[3]), "=f"(d[4]), "=f"(d[5]), "=f"(d[6]), "=f"(d[7]), "=f"(d[8]), "=f"(d[9]), "=f"(d[10]), "=f"(d[11]), "=f"(d[12]), "=f"(d[13]), "=f"(d[14]), "=f"(d[15]), "=f"(d[16]), "=f"(d[17]), "=f"(d[18]), "=f"(d[19]), "=f"(d[20]), "=f"(d[21]), "=f"(d[22]), "=f"(d[23]), "=f"(d[24]), "=f"(d[25]), "=f"(d[26]), "=f"(d[27]), "=f"(d[28]), "=f"(d[29]), "=f"(d[30]), "=f"(d[31]), "=f"(d[32]), "=f"(d[33]), "=f"(d[34]), "=f"(d[35]), "=f"(d[36]), "=f"(d[37]), "=f"(d[38]), "=f"(d[39]), "=f"(d[40]), "=f"(d[41]), "=f"(d[42]), "=f"(d[43]), "=f"(d[44]), "=f"(d[45]), "=f"(d[46]), "=f"(d[47]), "=f"(d[48]), "=f"(d[49]), "=f"(d[50]), "=f"(d[51]), "=f"(d[52]), "=f"(d[53]), "=f"(d[54]), "=f"(d[55]), "=f"(d[56]), "=f"(d[57]), "=f"(d[58]), "=f"(d[59]), "=f"(d[60]), "=f"(d[61]), "=f"(d[62]), "=f"(d[63]), "=f"(d[64]), "=f"(d[65]), "=f"(d[66]), "=f"(d[67]), "=f"(d[68]), "=f"(d[69]), "=f"(d[70]), "=f"(d[71]), "=f"(d[72]), "=f"(d[73]), "=f"(d[74]), "=f"(d[75]), "=f"(d[76]), "=f"(d[77]), "=f"(d[78]), "=f"(d[79]), "=f"(d[80]), "=f"(d[81]), "=f"(d[82]), "=f"(d[83]), "=f"(d[84]), "=f"(d[85]), "=f"(d[86]), "=f"(d[87]), "=f"(d[88]), "=f"(d[89]), "=f"(d[90]), "=f"(d[91]), "=f"(d[92]), "=f"(d[93]), "=f"(d[94]), "=f"(d[95])
     : "l"(da), "l"(db), "n"(TB), "n"(TA));
  } else {
    asm volatile("wgmma.mma_async.sync.aligned.m64n192k16.f32.bf16.bf16 {%0, %1, %2, %3, %4, %5, %6, %7, %8, %9, %10, %11, %12, %13, %14, %15, %16, %17, %18, %19, %20, %21, %22, %23, %24, %25, %26, %27, %28, %29, %30, %31, %32, %33, %34, %35, %36, %37, %38, %39, %40, %41, %42, %43, %44, %45, %46, %47, %48, %49, %50, %51, %52, %53, %54, %55, %56, %57, %58, %59, %60, %61, %62, %63, %64, %65, %66, %67, %68, %69, %70, %71, %72, %73, %74, %75, %76, %77, %78, %79, %80, %81, %82, %83, %84, %85, %86, %87, %88, %89, %90, %91, %92, %93, %94, %95}, %96, %97, 1, 1, 1, %99, %98;"
     : "+f"(d[0]), "+f"(d[1]), "+f"(d[2]), "+f"(d[3]), "+f"(d[4]), "+f"(d[5]), "+f"(d[6]), "+f"(d[7]), "+f"(d[8]), "+f"(d[9]), "+f"(d[10]), "+f"(d[11]), "+f"(d[12]), "+f"(d[13]), "+f"(d[14]), "+f"(d[15]), "+f"(d[16]), "+f"(d[17]), "+f"(d[18]), "+f"(d[19]), "+f"(d[20]), "+f"(d[21]), "+f"(d[22]), "+f"(d[23]), "+f"(d[24]), "+f"(d[25]), "+f"(d[26]), "+f"(d[27]), "+f"(d[28]), "+f"(d[29]), "+f"(d[30]), "+f"(d[31]), "+f"(d[32]), "+f"(d[33]), "+f"(d[34]), "+f"(d[35]), "+f"(d[36]), "+f"(d[37]), "+f"(d[38]), "+f"(d[39]), "+f"(d[40]), "+f"(d[41]), "+f"(d[42]), "+f"(d[43]), "+f"(d[44]), "+f"(d[45]), "+f"(d[46]), "+f"(d[47]), "+f"(d[48]), "+f"(d[49]), "+f"(d[50]), "+f"(d[51]), "+f"(d[52]), "+f"(d[53]), "+f"(d[54]), "+f"(d[55]), "+f"(d[56]), "+f"(d[57]), "+f"(d[58]), "+f"(d[59]), "+f"(d[60]), "+f"(d[61]), "+f"(d[62]), "+f"(d[63]), "+f"(d[64]), "+f"(d[65]), "+f"(d[66]), "+f"(d[67]), "+f"(d[68]), "+f"(d[69]), "+f"(d[70]), "+f"(d[71]), "+f"(d[72]), "+f"(d[73]), "+f"(d[74]), "+f"(d[75]), "+f"(d[76]), "+f"(d[77]), "+f"(d[78]), "+f"(d[79]), "+f"(d[80]), "+f"(d[81]), "+f"(d[82]), "+f"(d[83]), "+f"(d[84]), "+f"(d[85]), "+f"(d[86]), "+f"(d[87]), "+f"(d[88]), "+f"(d[89]), "+f"(d[90]), "+f"(d[91]), "+f"(d[92]), "+f"(d[93]), "+f"(d[94]), "+f"(d[95])
     : "l"(da), "l"(db), "n"(TB), "n"(TA));
  }
}

__device__ __forceinline__ uint32_t clock32() { uint32_t t; asm volatile("mov.u32 %0, %%clock;" : "=r"(t)); return t; }
__device__ __forceinline__ bool elect_one() {
  uint32_t pred;
  asm volatile("{\n.reg .pred p;\nelect.sync _|p, 0xffffffff;\nselp.u32 %0, 1, 0, p;\n}" : "=r"(pred));
  return pred != 0;
}
__device__ __forceinline__ void mbar_init(uint32_t b, int c) { asm volatile("mbarrier.init.shared::cta.b64 [%0], %1;" ::"r"(b), "r"(c) : "memory"); }
__device__ __forceinline__ void mbar_expect(uint32_t b, int bytes) { asm volatile("mbarrier.arrive.expect_tx.shared::cta.b64 _, [%0], %1;" ::"r"(b), "r"(bytes) : "memory"); }
__device__ __forceinline__ void mbar_arrive(uint32_t b) { asm volatile("mbarrier.arrive.shared::cta.b64 _, [%0];" ::"r"(b) : "memory"); }
__device__ __forceinline__ void mbar_arrive_if(uint32_t b, uint32_t pred) {
  asm volatile("{\n.reg .pred p;\nsetp.ne.u32 p, %1, 0;\n@p mbarrier.arrive.shared::cta.b64 _, [%0];\n}" ::"r"(b), "r"(pred) : "memory");
}
#define WAIT_LIMIT "2000000"
#define DIE_ADDR "l"(0ull)
#define DIE_ST "st.global.u32 [%2], %1;\n"
__device__ __forceinline__ void die() { asm volatile("st.global.u32 [%0], %1;" ::"l"(0ull), "r"(0) : "memory"); }
__device__ __forceinline__ void mbar_wait(uint32_t b, uint32_t ph) {
  asm volatile(
      "{\n.reg .pred p;\n.reg .u32 c;\nmov.u32 c, 0;\n"
      "W:\nmbarrier.try_wait.parity.shared::cta.b64 p, [%0], %1, 1000;\n@p bra D;\n"
      "add.u32 c, c, 1;\nsetp.lt.u32 p, c, " WAIT_LIMIT ";\n@p bra W;\n" DIE_ST
      "D:\n}" ::"r"(b), "r"(ph), DIE_ADDR : "memory");
}
__device__ __forceinline__ uint32_t mbar_test(uint32_t b, uint32_t ph) {
  uint32_t ok;
  asm volatile("{\n.reg .pred p;\nmbarrier.test_wait.parity.shared::cta.b64 p, [%1], %2;\nselp.u32 %0, 1, 0, p;\n}" : "=r"(ok) : "r"(b), "r"(ph) : "memory");
  return ok;
}
__device__ __forceinline__ void cnt_arrive(int idx) {
  asm volatile("red.release.gpu.global.add.u32 [%0], 1;" ::"l"(&g_cnt[idx * CNT_STRIDE]) : "memory");
}
__device__ __forceinline__ void cnt_wait(uint32_t idx, uint32_t target) {
  asm volatile(
      "{\n.reg .pred p;\n.reg .u32 c, v;\nmov.u32 c, 0;\n"
      "W:\nld.acquire.gpu.global.u32 v, [%3];\nsub.u32 v, v, %1;\nsetp.ge.s32 p, v, 0;\n@p bra D;\n"
      "add.u32 c, c, 1;\nsetp.lt.u32 p, c, " WAIT_LIMIT ";\n@p bra W;\n" DIE_ST
      "D:\n}" ::"r"(idx | 0x80000000u), "r"(target), DIE_ADDR, "l"(&g_cnt[idx * CNT_STRIDE]) : "memory");
}
__device__ __forceinline__ void release_x(uint32_t fdone, uint32_t ph, int cnt, int n, uint32_t mask) {
#pragma unroll 1
  for (int k = 0; k < n;) {
    int e = k + __ffs(mask >> k);
    mbar_wait(fdone + 8 * (e - 1), ph);
    asm volatile("fence.release.gpu;" ::: "memory");
    asm volatile("red.relaxed.gpu.global.add.u32 [%0], 1;" ::"l"(&g_cnt[(cnt + e - 1) * CNT_STRIDE]) : "memory");
    k = e;
  }
}
__device__ __forceinline__ uint4 lds128(uint32_t a) {
  uint4 v;
  asm volatile("ld.shared.v4.u32 {%0,%1,%2,%3}, [%4];" : "=r"(v.x), "=r"(v.y), "=r"(v.z), "=r"(v.w) : "r"(a) : "memory");
  return v;
}
__device__ __forceinline__ void stat_publish(ulonglong2* p, float s, float qq, uint32_t ep1) {
  const float mean = s * (1.0f / DM);
  const float rstd = rsqrtf(fmaxf(qq * (1.0f / DM) - mean * mean, 0.f) + 1e-5f);
  const unsigned long long tag = (unsigned long long)ep1 << 32;
  asm volatile("st.relaxed.gpu.global.v2.u64 [%0], {%1, %2};" ::"l"(p), "l"(tag | __float_as_uint(rstd)), "l"(tag | __float_as_uint(-mean)) : "memory");
}
__device__ __forceinline__ void stat_gather(const ulonglong2* p, uint32_t tag, float* rsd, float* md, float* rs2) {
  unsigned long long a[4], b[4];
#pragma unroll 1
  for (uint32_t it = 0;; it++) {
    bool ok = true;
#pragma unroll
    for (int i = 0; i < 4; i++) asm volatile("ld.relaxed.gpu.global.v2.u64 {%0, %1}, [%2];" : "=l"(a[i]), "=l"(b[i]) : "l"(p + i * 32) : "memory");
#pragma unroll
    for (int i = 0; i < 4; i++) ok = ok && (uint32_t)(a[i] >> 32) == tag && (uint32_t)(b[i] >> 32) == tag;
    if (ok) break;
    if (it > 2000000u) { die(); break; }
  }
#pragma unroll
  for (int i = 0; i < 4; i++) {
    rsd[(i & 1) * 64 + (i >> 1) * 2] = __uint_as_float((uint32_t)a[i]);
    if (md) md[(i & 1) * 64 + (i >> 1) * 2] = __uint_as_float((uint32_t)b[i]);
    if (rs2) rs2[i * 8] = __uint_as_float((uint32_t)a[i]);
  }
}
__device__ __forceinline__ void pace(uint32_t t0, uint32_t dt) { while (clock32() - t0 < dt) __nanosleep(20); }
__device__ __forceinline__ void spin_until(uint32_t t) {
  asm volatile("{\n.reg .pred p;\n.reg .u32 c;\nW:\nmov.u32 c, %%clock;\nsub.u32 c, c, %0;\nsetp.lt.s32 p, c, 0;\n@p nanosleep.u32 40;\n@p bra W;\n}" ::"r"(t) : "memory");
}
__device__ __forceinline__ void tma2d(uint32_t dst, const CUtensorMap* m, uint32_t bar, int c0, int c1) {
  asm volatile("cp.async.bulk.tensor.2d.shared::cluster.global.mbarrier::complete_tx::bytes [%0], [%1, {%3, %4}], [%2];" ::"r"(dst), "l"(m), "r"(bar), "r"(c0), "r"(c1) : "memory");
}
__device__ __forceinline__ void tma2d_ef(uint32_t dst, const CUtensorMap* m, uint32_t bar, int c0, int c1) {
  asm volatile("{\n.reg .b64 pol;\ncreatepolicy.fractional.L2::evict_first.b64 pol, 1.0;\n"
               "cp.async.bulk.tensor.2d.shared::cluster.global.mbarrier::complete_tx::bytes.L2::cache_hint [%0], [%1, {%3, %4}], [%2], pol;\n}"
               ::"r"(dst), "l"(m), "r"(bar), "r"(c0), "r"(c1) : "memory");
}
__device__ __forceinline__ void tma3d(uint32_t dst, const CUtensorMap* m, uint32_t bar, int c0, int c1, int c2) {
  asm volatile("cp.async.bulk.tensor.3d.shared::cluster.global.mbarrier::complete_tx::bytes [%0], [%1, {%3, %4, %5}], [%2];" ::"r"(dst), "l"(m), "r"(bar), "r"(c0), "r"(c1), "r"(c2) : "memory");
}
__device__ __forceinline__ void tma3d_mc(uint32_t dst, const CUtensorMap* m, uint32_t bar, int c0, int c1, int c2) {
  asm volatile("cp.async.bulk.tensor.3d.shared::cluster.global.mbarrier::complete_tx::bytes.multicast::cluster [%0], [%1, {%3, %4, %5}], [%2], %6;"
               ::"r"(dst), "l"(m), "r"(bar), "r"(c0), "r"(c1), "r"(c2), "h"((uint16_t)3) : "memory");
}
__device__ __forceinline__ uint32_t map_rank(uint32_t a, uint32_t rank) {
  uint32_t v;
  asm("mapa.shared::cluster.u32 %0, %1, %2;" : "=r"(v) : "r"(a), "r"(rank));
  return v;
}
__device__ __forceinline__ void mbar_arrive_cl_if(uint32_t b, uint32_t pred) {
  asm volatile("{\n.reg .pred p;\nsetp.ne.u32 p, %1, 0;\n@p mbarrier.arrive.shared::cluster.b64 _, [%0];\n}" ::"r"(b), "r"(pred) : "memory");
}
__device__ __forceinline__ void bulk_pf(const void* p, int bytes) {
  asm volatile("cp.async.bulk.prefetch.L2.global [%0], %1;" ::"l"(p), "r"(bytes) : "memory");
}
__device__ __forceinline__ void tma_st2d(const CUtensorMap* m, uint32_t src, int c0, int c1) {
  asm volatile("cp.async.bulk.tensor.2d.global.shared::cta.tile.bulk_group [%0, {%2, %3}], [%1];" ::"l"(m), "r"(src), "r"(c0), "r"(c1) : "memory");
}
__device__ __forceinline__ void tma_red2d(const CUtensorMap* m, uint32_t src, int c0, int c1) {
  asm volatile("cp.reduce.async.bulk.tensor.2d.global.shared::cta.add.tile.bulk_group [%0, {%2, %3}], [%1];" ::"l"(m), "r"(src), "r"(c0), "r"(c1) : "memory");
}
__device__ __forceinline__ void bulk_commit() { asm volatile("cp.async.bulk.commit_group;" ::: "memory"); }
__device__ __forceinline__ void bulk_wait0() { asm volatile("cp.async.bulk.wait_group 0;" ::: "memory"); }
__device__ __forceinline__ void fence_async_smem() { asm volatile("fence.proxy.async.shared::cta;" ::: "memory"); }
__device__ __forceinline__ void fence_async_global() { asm volatile("fence.proxy.async.global;" ::: "memory"); }
__device__ __forceinline__ void wg_fence() { asm volatile("wgmma.fence.sync.aligned;" ::: "memory"); }
__device__ __forceinline__ void wg_commit() { asm volatile("wgmma.commit_group.sync.aligned;" ::: "memory"); }
template <int N> __device__ __forceinline__ void wg_wait() { asm volatile("wgmma.wait_group.sync.aligned %0;" ::"n"(N) : "memory"); }
__device__ __forceinline__ uint32_t pk(float a, float b) {
  uint32_t r;
  asm("cvt.rn.bf16x2.f32 %0, %1, %2;" : "=r"(r) : "f"(b), "f"(a));
  return r;
}
__device__ __forceinline__ uint32_t pk_relu(float a, float b) {
  uint32_t r;
  asm("cvt.rn.relu.bf16x2.f32 %0, %1, %2;" : "=r"(r) : "f"(b), "f"(a));
  return r;
}
__device__ __forceinline__ float bf_lo(uint32_t v) { return __uint_as_float(v << 16); }
__device__ __forceinline__ float bf_hi(uint32_t v) { return __uint_as_float(v & 0xffff0000u); }
__device__ __forceinline__ void stsm4(uint32_t addr, uint32_t a0, uint32_t a1, uint32_t a2, uint32_t a3) {
  asm volatile("stmatrix.sync.aligned.m8n8.x4.shared.b16 [%0], {%1,%2,%3,%4};" ::"r"(addr), "r"(a0), "r"(a1), "r"(a2), "r"(a3));
}
template <int R> __device__ __forceinline__ void reg_fence(float (&d)[R]) {
#pragma unroll
  for (int i = 0; i < R; i++) asm volatile("" : "+f"(d[i])::"memory");
}
constexpr uint32_t DESC_HI_128 = (1024u >> 4) | (1u << 30);
__device__ __forceinline__ uint64_t desc(uint32_t lo, uint32_t hi) {
  uint64_t d;
  asm("mov.b64 %0, {%1, %2};" : "=l"(d) : "r"(lo), "r"(hi));
  return d;
}

__device__ __forceinline__ void sum8(uint4 v, float& s, float& q) {
  float a;
  a = bf_lo(v.x); s += a; q = fmaf(a, a, q);  a = bf_hi(v.x); s += a; q = fmaf(a, a, q);
  a = bf_lo(v.y); s += a; q = fmaf(a, a, q);  a = bf_hi(v.y); s += a; q = fmaf(a, a, q);
  a = bf_lo(v.z); s += a; q = fmaf(a, a, q);  a = bf_hi(v.z); s += a; q = fmaf(a, a, q);
  a = bf_lo(v.w); s += a; q = fmaf(a, a, q);  a = bf_hi(v.w); s += a; q = fmaf(a, a, q);
}

__device__ __forceinline__ int frag_pos(int row) { return (((row >> 4) & 3) * 8 + (row & 7)) * 4 + ((row >> 3) & 1) + (row >> 6) * 2; }
__device__ __forceinline__ float2 lds64f(uint32_t a) {
  float2 v;
  asm volatile("ld.shared.v2.f32 {%0,%1}, [%2];" : "=f"(v.x), "=f"(v.y) : "r"(a) : "memory");
  return v;
}
__device__ __forceinline__ float4 lds128f(uint32_t a) {
  float4 v;
  asm volatile("ld.shared.v4.f32 {%0,%1,%2,%3}, [%4];" : "=f"(v.x), "=f"(v.y), "=f"(v.z), "=f"(v.w) : "r"(a) : "memory");
  return v;
}

__device__ __forceinline__ int doff(int layer, int s) { return (layer && s == 3) ? OFF_A + 6 * A_SLOT : OFF_B + (s & 3) * D_SLOT; }

constexpr int G3A_C1 = 8;
constexpr int G3B_C1 = 6;
constexpr int G3A_C2 = 12;
constexpr int G3B_C2 = 10;
constexpr int CLD_DT = 900;
constexpr int FLUSH_DT = 800;
constexpr int FLUSH_DT_D = 450;
constexpr int CPF2_DT = 400;
constexpr int HPF_D_START = 66000;
constexpr int HW1_START = 10000;
constexpr int XEARLY4 = 6;
constexpr int FLUSH_DT4 = 870;
constexpr int RELMASK2 = 0x1AC;
constexpr int RELMASK4 = 0x12A;
constexpr int FLUSH_DT_A = 800;
constexpr int AG_DT = 200;
constexpr int CL0_T0 = 1000;
constexpr int REST_T0 = 700;
constexpr int CE1 = 5;
constexpr int CE1_DT = 1100;
constexpr int CL0_DT = 1250;
constexpr int CL0_DT2 = 1000;
constexpr int CL0_N = 6;
constexpr int HPF_W2A = 52000;
constexpr int YGAP = 150;
constexpr int X2_DT = 700;
constexpr int X2_DT2 = 300;
constexpr int FLUSH_DT_E = 820;

__global__ void __launch_bounds__(384, 1)
fnet_ffn_kernel(const __grid_constant__ Maps maps, const __nv_bfloat16* __restrict__ xin, const __nv_bfloat16* __restrict__ cre,
                const __nv_bfloat16* __restrict__ cim, const __nv_bfloat16* __restrict__ dre,
                const __nv_bfloat16* __restrict__ dim,
                __nv_bfloat16* xout) {
  extern __shared__ __align__(1024) unsigned char smem[];
  const uint32_t sb = __shfl_sync(0xffffffffu, (uint32_t)__cvta_generic_to_shared(smem), 0);
  constexpr uint32_t sbd = 1024;
  const int tid = threadIdx.x;
  const int wg = __shfl_sync(0xffffffffu, tid >> 7, 0);
  const int warp = __shfl_sync(0xffffffffu, (tid >> 5) & 3, 0);
  const int lane = tid & 31;
  if (blockIdx.x < NHELP) {
    if (tid == 0) atomicAdd(&g_cnt[CNT_TICKET * CNT_STRIDE], 1u);
    const uint32_t th0 = clock32();
    constexpr int HS = 16, HG = DFF / 192 / NHELP;
    const uint32_t hb = sb + HS * B_SLOT + 8192;
    if (tid == 0) {
#pragma unroll
      for (int i = 0; i < 2 * HS; i++) mbar_init(hb + 8 * i, 1);
      asm volatile("fence.mbarrier_init.release.cluster;" ::: "memory");
    }
    for (int i = tid; i < 2048; i += 384) reinterpret_cast<uint32_t*>(smem + HS * B_SLOT)[i] = 0x3f803f80u;
    fence_async_smem();
    __syncthreads();
    if (wg == 0) {
      int slot = 0, ph = 0;
#pragma unroll 1
      for (int g = 0; g < HG; g++) {
        float acc[96];
#pragma unroll
        for (int i = 0; i < 96; i++) acc[i] = 0.f;
#pragma unroll 1
        for (int st = 0; st < 18; st++) {
          mbar_wait(hb + 8 * slot, ph);
          const uint32_t blo = (((sbd + slot * B_SLOT) >> 4) | ((4096u >> 4) << 16));
          const uint64_t da = desc(((sbd + HS * B_SLOT) >> 4) | (1u << 16), DESC_HI_128);
          wg_fence();
          wgmma_n192<1, false>(acc, da, desc(blo, DESC_HI_128));
          wgmma_n192<1, false>(acc, da, desc(blo + 128, DESC_HI_128));
          wg_commit();
          wg_wait<1>();
          mbar_arrive_if(hb + 8 * (HS + ((slot + HS - 1) & (HS - 1))), tid == 0 && (g | st));
          if (++slot == HS) { slot = 0; ph ^= 1; }
        }
        wg_wait<0>();
        reg_fence(acc);
        if (tid < 4) {
#pragma unroll
          for (int b = 0; b < 24; b++)
            *reinterpret_cast<float2*>(g_cs1 + ((blockIdx.x * HG + g) / 3) * 576 + tid * 144 + (g % 3) * 48 + b * 2) = make_float2(acc[b * 4], acc[b * 4 + 1]);
        }
      }
      __syncwarp();
      if (tid == 0) { cnt_arrive(CNT_CS); }
    } else if (tid == 128) {
      int slot = 0, ph = 1;
      pace(th0, HW1_START);
#pragma unroll 1
      for (int i = 0; i < HG * 18; i++) {
        mbar_wait(hb + 8 * (HS + slot), ph);
        mbar_expect(hb + 8 * slot, B_SLOT);
        tma3d(sb + slot * B_SLOT, &maps.w1, hb + 8 * slot, 0, (i % 18) * 32, (blockIdx.x * HG + i / 18) * 3);
        if (++slot == HS) { slot = 0; ph ^= 1; }
      }
      pace(th0, HPF_W2A);
#pragma unroll 1
      for (int i = 0; i < 108; i++)
        asm volatile("cp.async.bulk.prefetch.tensor.3d.L2.global.tile [%0, {%1, %2, %3}];"
                     ::"l"(&maps.w2n), "r"(0), "r"(blockIdx.x * 1152 + (i % 12) * 96), "r"(i / 12) : "memory");
      pace(th0, HPF_D_START);
#pragma unroll 1
      for (int i = 0; i < 81; i++) bulk_pf(reinterpret_cast<const char*>((blockIdx.x & 1) ? dim : dre) + ((blockIdx.x >> 1) * 81 + i) * 4096, 4096);
    }
    return;
  }
  const int cta = blockIdx.x - NHELP;
  const int r = cta & 15, p = cta >> 4;
  const int m = p >> 2, q = p & 3;
  const int rank = cta & 1;
  const uint32_t bar0 = sb + OFF_BAR;
#define BAR(i) (bar0 + 8u * (uint32_t)(i))
#define START_SYNC() do { __syncwarp(); asm volatile("barrier.cluster.wait.acquire.aligned;" ::: "memory"); } while (0)

  uint32_t ticket = 0;
  if (elect_one()) {
    const int w12 = wg * 4 + warp;
#pragma unroll
    for (int i = 0; i < 16; i++) mbar_init(BAR(w12 * 16 + i), w12 < 2 ? 4 : (w12 == 2 ? 2 : 1));
    if (w12 == 10) {
#pragma unroll
      for (int i = 0; i < 8; i++) mbar_init(BAR(BAR_ABOK + i), 1);
    }
    asm volatile("fence.mbarrier_init.release.cluster;" ::: "memory");
    if (w12 == 8) {
      fence_async_smem();
      mbar_expect(BAR(BAR_XF), A_SLOT);
      tma2d(sb + OFF_A, &maps.xin, BAR(BAR_XF), 0, r * 128);
    }
  }
  __syncwarp();
  asm volatile("barrier.cluster.arrive.relaxed.aligned;" ::: "memory");
  if (wg == 2 && warp == 0) {
    START_SYNC();
    if (elect_one()) {
#pragma unroll 1
      for (int k = 0; k < 4; k++) {
        mbar_expect(BAR(BAR_DF + k), D_SLOT);
        if ((k & 1) == rank) tma3d_mc(sb + OFF_B + k * D_SLOT, m ? &maps.di : &maps.dr, BAR(BAR_DF + k), k * 64, q * 48, 0);
        mbar_expect(BAR(BAR_XF + k + 1), A_SLOT);
        tma2d(sb + OFF_A + (k + 1) * A_SLOT, &maps.xin, BAR(BAR_XF + k + 1), (k + 1) * 64, r * 128);
      }
    }
    __syncwarp();
  }
  if (tid == 320) asm volatile("atom.relaxed.gpu.global.add.u32 %0, [%1], 1;" : "=r"(ticket) : "l"(&g_cnt[CNT_TICKET * CNT_STRIDE]));

  if (wg == 2) {
    asm volatile("setmaxnreg.dec.sync.aligned.u32 40;");
    if (warp & 1) START_SYNC();
    if (warp == 0) {
      const CUtensorMap* mD = m ? &maps.di : &maps.dr;
      if (elect_one()) {
        int slot = 0, ph = 1;
#pragma unroll 1
        for (int layer = 0; layer < 2; layer++) {
#pragma unroll 1
          for (int s = 0; s < 9; s++) {
            if (s < 3) {
              const int nacq = (layer && s == 1) ? 1 : 2;
#pragma unroll 1
              for (int i = 0; i < nacq; i++) {
                mbar_wait(BAR(BAR_BEMPTY + slot), ph);
                mbar_arrive(BAR(BAR_BFULL + slot));
                if (++slot == NB + 1 - layer) { slot = 0; ph ^= 1; }
              }
            } else if (layer && s == 7) {
              mbar_wait(BAR(BAR_SENTY), 0);
              mbar_arrive_cl_if(map_rank(BAR(BAR_STGF), 0), 1);
              mbar_arrive_cl_if(map_rank(BAR(BAR_STGF), 1), 1);
              mbar_wait(BAR(BAR_STGF), 0);
            } else if (s > 3) {
              mbar_wait(BAR(BAR_DREL + s - 4), layer);
            }
            if (layer || s >= 4) {
              mbar_expect(BAR(BAR_DF + s), D_SLOT);
              if ((s & 1) == rank) tma3d_mc(sb + doff(layer, s), mD, BAR(BAR_DF + s), s * 64, q * 48, 0);
              const int k = s + 1;
              if (layer == 0 && k < 9) {
                mbar_expect(BAR(BAR_XF + k), A_SLOT);
                tma2d(sb + OFF_A + k * A_SLOT, &maps.xin, BAR(BAR_XF + k), k * 64, r * 128);
              }
            }
          }
#pragma unroll 1
          for (int sg = -8; sg < 18; sg++) {
            const CUtensorMap* mm;
            int row, atom, n, dk = 32, dk2 = 0;
            if (sg < 4) {
              mm = &maps.abld; row = (layer * 2 + m) * SEQ + q * 512;
              if (sg < 0) {
                mbar_wait(BAR(BAR_ABOK + 8 + sg), layer);
                row += (sg & 3) * 128 + (sg & 4) * 16; atom = 0; n = 2;
              } else {
                if (!(sg & 1)) mbar_wait(BAR(sg ? BAR_FOK : BAR_AB1), layer);
                row += (sg & 1) * 64; atom = (sg >> 1) * 3 + 3; n = 8; dk2 = 64;
              }
            } else if (sg < 13) {
              mm = &maps.w1;
              if (sg < 10) {
                const int cw = sg & 1;
                const int c1 = cw ? G3B_C1 : G3A_C1, c2 = cw ? G3B_C2 : G3A_C2;
                const int lo = sg < 6 ? 0 : (sg < 8 ? c1 : c2), hi = sg < 6 ? c1 : (sg < 8 ? c2 : 18);
                atom = p * 9 + cw * 3; row = lo * 32; n = hi - lo;
              } else { atom = p * 9 + 6; row = (12 - sg) * 192; n = 6; }
            } else {
              row = p * 576;
              atom = (sg - 13) * 2;
              if (sg < 17) { mm = &maps.w2; n = 12; dk = 48; }
              else { mm = &maps.w2n; n = 6; dk = 96; }
            }
            const uint32_t fb0 = BAR(BAR_BFULL);
            const int nsl = sg < 13 ? NB + 1 : NB;
            if (sg == 13) {
              mbar_wait(BAR(BAR_BEMPTY), ph);
              mbar_arrive(BAR(BAR_BFULL));
              mbar_arrive_cl_if(map_rank(BAR(BAR_BEMPTY), 0), 1);
              mbar_arrive_cl_if(map_rank(BAR(BAR_BEMPTY), 1), 1);
              slot = 1;
            }
            if (sg == 17) asm volatile("prefetch.tensormap [%0];" ::"l"(mD) : "memory");
            if (sg == -6) mbar_wait(BAR(BAR_STG2), layer);
#pragma unroll 1
            for (int i = 0; i < n; i++) {
              mbar_wait(BAR(BAR_BEMPTY + slot), ph);
              mbar_expect(fb0 + 8 * slot, B_SLOT);
              if ((i & 1) == rank) tma3d_mc(sb + OFF_B + slot * B_SLOT, mm, fb0 + 8 * slot, 0, row, atom);
              row += dk + (i & 1) * dk2;
              if (++slot == nsl) { slot = 0; ph ^= 1; }
            }
          }
        }
#pragma unroll 1
        for (int i = 0; i < NB; i++) {
          mbar_wait(BAR(BAR_BEMPTY + slot), ph);
          if (++slot == NB) { slot = 0; ph ^= 1; }
        }
      }
    } else if (warp == 1) {
      if (lane == 0) {
        asm volatile("prefetch.tensormap [%0];" ::"l"(m ? &maps.ci : &maps.cr) : "memory");
        asm volatile("prefetch.tensormap [%0];" ::"l"(&maps.abst) : "memory");
        asm volatile("prefetch.tensormap [%0];" ::"l"(&maps.abld) : "memory");
      }
      mbar_wait(BAR(BAR_EPOCH), 0);
      const uint32_t ep1 = *reinterpret_cast<volatile uint32_t*>(smem + OFF_EPOCH);
      {
        unsigned long long a[3], b[3];
#pragma unroll 1
        for (uint32_t it = 0;; it++) {
          bool ok = true;
#pragma unroll
          for (int i = 0; i < 3; i++)
            asm volatile("ld.relaxed.gpu.global.v2.u64 {%0, %1}, [%2];" : "=l"(a[i]), "=l"(b[i]) : "l"(&g_csd[p * 144 + min(lane + i * 32, 71) * 2]) : "memory");
#pragma unroll
          for (int i = 0; i < 3; i++) ok = ok && (uint32_t)(a[i] >> 32) == ep1 && (uint32_t)(b[i] >> 32) == ep1;
          if (ok) break;
          if (it > 2000000u) { die(); break; }
        }
#pragma unroll
        for (int i = 0; i < 3; i++)
          reinterpret_cast<float2*>(smem + OFF_CSD)[(min(lane + i * 32, 71) & 3) * 18 + (min(lane + i * 32, 71) >> 2)] = make_float2(__uint_as_float((uint32_t)a[i]), __uint_as_float((uint32_t)b[i]));
        __syncwarp();
        mbar_arrive_if(BAR(BAR_CSD), lane == 0);
      }
      if (lane == 0) {
#pragma unroll 1
        for (int layer = 0; layer < 2; layer++) {
          const int abrow = (layer * 2 + m) * SEQ + r * 128;
          const int abcnt = CNT_AB + ((layer * 2 + m) * 16 + r) * 4 + 1;
          mbar_wait(BAR(BAR_ABH), layer);
          cnt_arrive(abcnt - 1);
          mbar_wait(BAR(BAR_ABH + 1), layer);
          cnt_arrive(abcnt);
          mbar_wait(BAR(BAR_ABSTG), layer);
          mbar_wait(BAR(BAR_ABOK), layer);
          spin_until(clock32() + REST_T0);
          tma_st2d(&maps.abst, sb + OFF_A + 7 * A_SLOT, 192 + q * 48, abrow);
          bulk_commit();
          bulk_wait0();
          mbar_arrive(BAR(BAR_A7));
          cnt_arrive(abcnt + 1);
          tma_st2d(&maps.abst, sb + OFF_A + 8 * A_SLOT, 384 + q * 48, abrow);
          bulk_commit();
          bulk_wait0();
          mbar_arrive(BAR(BAR_A8));
          cnt_arrive(abcnt + 2);
          release_x(BAR(BAR_FDONE), layer, CNT_X + (layer * 2 * 16 + r) * 9, 6, RELMASK2);
          {
            uint32_t tn = 0;
#pragma unroll 1
            for (int i = 0; i < 8; i++) {
              if ((i & 3) == 0) mbar_wait(BAR(BAR_FDONE + 7 + (i >> 2)), layer);
              if (i == 0) tn = clock32();
              spin_until(tn);
              tma_red2d(&maps.xred, sb + OFF_A + 7 * A_SLOT + i * 4096, 448 + (i >> 2) * 64, r * 128 + (i & 3) * 32);
              tma_red2d(&maps.xred, sb + OFF_A + 7 * A_SLOT + i * 4096 + 2048, 448 + (i >> 2) * 64, r * 128 + (i & 3) * 32 + 16);
              tn += AG_DT;
              if (i == 3) {
                bulk_commit();
                mbar_wait(BAR(BAR_FDONE + 6), layer);
                bulk_wait0();
                mbar_arrive(BAR(BAR_SENT));
              }
            }
            bulk_commit();
            bulk_wait0();
            cnt_arrive(CNT_X + (layer * 2 * 16 + r) * 9 + 8);
          }
          mbar_wait(BAR(BAR_XRD), layer);
#pragma unroll 1
          for (int s = 0; s < 3; s++) {
            mbar_wait(BAR(BAR_RG3C + s), layer);
            mbar_wait(BAR(BAR_RG3B + 6 + s), layer);
            mbar_expect(BAR(BAR_X1F + 9 + s), A_SLOT);
            tma2d(sb + OFF_A + (6 + s) * A_SLOT, &maps.xld, BAR(BAR_X1F + 9 + s), s * 64, r * 128);
          }
#pragma unroll 1
          for (int s = 0; s < 3; s++) mbar_wait(BAR(BAR_X1F + 9 + s), layer);
          cnt_arrive(CNT_G3 + layer * 16 + r);
          cnt_wait(CNT_G3 + layer * 16 + r, ep1 * 8);
          mbar_arrive(BAR(BAR_FOK + 1));
          if (layer == 0) release_x(BAR(BAR_FDONE + 9), 0, CNT_X + (16 + r) * 9, 6, RELMASK4);
          asm volatile("prefetch.tensormap [%0];" ::"l"(&maps.xh) : "memory");
          mbar_wait(BAR(BAR_FDONE + 17), layer);
          tma_red2d(&maps.xh, sb + OFF_A + 8 * A_SLOT, 512, r * 128);
          if (layer == 0) {
            bulk_commit();
            mbar_wait(BAR(BAR_FDONE + 15), 0);
            bulk_wait0();
            mbar_arrive(BAR(BAR_SENTX));
            mbar_wait(BAR(BAR_FDONE + 16), 0);
            spin_until(clock32() + YGAP);
#pragma unroll 1
            for (int i = 0; i < 8; i++) tma_red2d(&maps.xred, sb + OFF_STG + i * 2048, 384 + (i & 1) * 64, r * 128 + 64 + (i >> 1) * 16);
            bulk_commit();
          }
          tma_red2d(&maps.xh, sb + OFF_A + 8 * A_SLOT + 8192, 512, r * 128 + 64);
          bulk_commit();
          if (layer == 0) {
            asm volatile("cp.async.bulk.wait_group 1;" ::: "memory");
            mbar_arrive(BAR(BAR_SENTY));
          }
          bulk_wait0();
          if (layer == 0) {
            cnt_arrive(CNT_X + (16 + r) * 9 + 8);
          }
        }
      }
    } else if (warp == 2) {
      START_SYNC();
      if ((sb & 0x3FFFFu) != sbd) die();
      const uint32_t ep1 = __shfl_sync(0xffffffffu, ticket, 0) / NGRID + 1;
      if (lane == 0) {
        *reinterpret_cast<volatile uint32_t*>(smem + OFF_EPOCH) = ep1;
        mbar_arrive(BAR(BAR_EPOCH));
      }
      {
        stat_gather(&g_stat[r * 128 + lane], ep1, reinterpret_cast<float*>(smem + OFF_RS) + frag_pos(lane), reinterpret_cast<float*>(smem + OFF_MEAN) + frag_pos(lane), nullptr);
        __syncwarp();
        mbar_arrive_if(BAR(BAR_STAT), lane == 0);
        mbar_arrive_if(BAR(BAR_STATY), lane == 0);
      }
#pragma unroll 1
      for (int ph4 = 0; ph4 < 4; ph4++) {
        const int layer = ph4 >> 1, second = ph4 & 1;
        if (ph4) {
          const bool low = !second && lane >= 9;
          const int pl = (ph4 - 1) >> 1, k = min(low ? lane - 3 : lane, 8);
          const uint32_t fd = BAR(BAR_FDONE + (second ? 0 : 9));
          const uint32_t fr = BAR(second ? (k < 8 ? BAR_RG2 + k : BAR_RG1 + 8) : (k < 8 ? BAR_RG1 + 3 : BAR_RG4 + 8));
          const uint32_t fp = second ? pl : k < 8;
          const uint32_t fb = BAR(low ? BAR_XFY - 6 + k : (second ? BAR_X1F : BAR_XF) + k);
          const int kr = k - 1 + __ffs((second ? RELMASK2 : RELMASK4) >> k);
          const uint32_t* flag = &g_cnt[(CNT_X + ((ph4 - 1) * 16 + r) * 9 + kr - (!second && !low && k >= 6)) * CNT_STRIDE];
          uint32_t state = lane >= (second ? 9 : 12) ? 2 : 0;
          bool needm = second;
          uint32_t tgo = 0;
          if (second) { mbar_wait(BAR(BAR_STAT), layer); mbar_wait(BAR(BAR_STATY), layer); }
          mbar_wait(fd, pl);
#pragma unroll 1
          for (uint32_t it = 0;; it++) {
            bool polled = false;
            if (state == 0 && mbar_test(fd + 8 * kr, pl)) {
              uint32_t c;
              asm volatile("ld.acquire.gpu.global.u32 %0, [%1];" : "=r"(c) : "l"(flag) : "memory");
              polled = true;
              if ((int32_t)(c - ep1 * 8) >= 0) {
                fence_async_global();
                state = 1;
                tgo = clock32() + (second ? (k < 3 ? k * X2_DT : (kr - k < 2 && k < 8 && k > 3 ? (1 - (kr - k)) * X2_DT2 : 0)) : 0);
                if (!second && k < XEARLY4) { mbar_arrive(BAR(BAR_XOK + k)); state = 2; }
              }
            }
            if (state == 1 && (int32_t)(clock32() - tgo) >= 0 && mbar_test(fr, fp)) {
              mbar_expect(fb, second ? A_SLOT : A_SLOT / 2);
              tma2d(sb + OFF_A + k * A_SLOT + low * 8192, second ? &maps.xld : &maps.xh, fb, k * 64, r * 128 + low * 64);
              state = 2;
            }
            if (needm && (__ballot_sync(0xffffffffu, state != 0) & 0xff) == 0xff) {
              __syncwarp();
              float4 t;
              asm volatile("ld.relaxed.gpu.global.v4.f32 {%0,%1,%2,%3}, [%4];" : "=f"(t.x), "=f"(t.y), "=f"(t.z), "=f"(t.w) : "l"(&g_rsum[layer * SEQ + r * 128 + lane * 4]) : "memory");
              float4* mp = reinterpret_cast<float4*>(smem + OFF_MEAN) + lane;
              const float4 o = *mp;
              constexpr float inv = -1.0f / DM;
              *mp = make_float4(fmaf(t.x, inv, o.x), fmaf(t.y, inv, o.y), fmaf(t.z, inv, o.z), fmaf(t.w, inv, o.w));
              __syncwarp();
              mbar_arrive_if(BAR(BAR_STAT + 1), lane == 0);
              needm = false;
            }
            if (__all_sync(0xffffffffu, state == 2)) break;
            if (!__any_sync(0xffffffffu, polled)) __nanosleep(100);
            if (it > 4000000u) { die(); break; }
          }
        }
        if (!second) {
          int idx = CNT_AB + ((layer * 2 + m) * 16 + q * 4 + (lane & 3)) * 4 + (lane >> 2);
          uint32_t target = ep1 * 4;
          if (lane == 16 || lane == 17) idx = CNT_AB + ((layer * 2 + lane - 16) * 16 + r) * 4 + 1;
          if (lane == 18) { idx = CNT_XINIT + r; target = ep1 * 32; }
          uint32_t pend = lane < 19, pm = 0x7ffff;
          mbar_wait(BAR(BAR_RG1 + 4), layer);
#pragma unroll 1
          for (uint32_t it = 0; pm; it++) {
            if (pend && (lane < 4 || !(pm & 15))) {
              uint32_t v;
              asm volatile("ld.acquire.gpu.global.u32 %0, [%1];" : "=r"(v) : "l"(&g_cnt[idx * CNT_STRIDE]) : "memory");
              if ((int32_t)(v - target) >= 0) {
                fence_async_global();
                if (lane < 8) mbar_arrive(BAR(BAR_ABOK + lane));
                pend = 0;
              }
            }
            __syncwarp();
            const uint32_t nm = __ballot_sync(0xffffffffu, pend);
            mbar_arrive_if(BAR(BAR_AB1), lane == 0 && (pm & 0xf00) && !(nm & 0xf00));
            pm = nm;
            if (it > 2000000u) { die(); break; }
          }
          __syncwarp();
          mbar_arrive_if(BAR(BAR_FOK), lane == 0);
        }
      }
    } else {
      const CUtensorMap* mC = m ? &maps.ci : &maps.cr;
      const char* cbase = reinterpret_cast<const char*>((m ? cim : cre) + (size_t)(r * 128 + (lane >> 1)) * SEQ + q * 512) + (lane & 1) * 128;
      asm volatile("prefetch.global.L2 [%0];" ::"l"(cbase));
      const int myrow = r * 128 + p * 16 + (lane >> 1);
      auto cload = [&](int k) {
        if (elect_one()) {
          mbar_expect(BAR(BAR_CF + k), A_SLOT);
          tma2d_ef(sb + OFF_A + k * A_SLOT, mC, BAR(BAR_CF + k), q * 512 + (k & 3) * 128 + (k >> 2) * 64, r * 128);
        }
        __syncwarp();
      };
      uint32_t t0 = clock32() + CL0_T0 + (cta & 3) * (CL0_DT / 4);
#pragma unroll 1
      for (int kc = 0; kc < 8; kc++) {
        if (kc == CL0_N) { mbar_wait(BAR(BAR_ABOK), 0); t0 = clock32() + (cta & 3) * (CL0_DT2 / 4); }
        spin_until(t0);
        t0 += kc < CL0_N ? CL0_DT : CL0_DT2;
        mbar_wait(BAR(kc < 7 ? BAR_RG1 + kc : BAR_A7), 0);
        cload(kc);
      }
      mbar_wait(BAR(BAR_EPOCH), 0);
      const uint32_t ep1 = *reinterpret_cast<volatile uint32_t*>(smem + OFF_EPOCH);
#pragma unroll 1
      for (int layer = 0; layer < 2; layer++) {
        if (layer) {
          if (elect_one()) {
#pragma unroll 1
            for (int kt = 0; kt < XEARLY4; kt++) {
              mbar_wait(BAR(BAR_XOK + kt), 0);
              mbar_wait(BAR(BAR_RG4 + kt), 0);
              mbar_expect(BAR(BAR_XF + kt), A_SLOT);
              tma2d(sb + OFF_A + kt * A_SLOT, &maps.xld, BAR(BAR_XF + kt), kt * 64, r * 128);
            }
            mbar_wait(BAR(BAR_SENTX), 0);
            cnt_arrive(CNT_X + (16 + r) * 9 + 7);
          }
          __syncwarp();
          t0 = clock32() + (cta & 3) * (CE1_DT / 4);
#pragma unroll 1
          for (int kc = 0; kc < 8; kc++) {
            if (kc == CE1) { mbar_wait(BAR(BAR_STATY), 1); mbar_wait(BAR(BAR_ABOK), 1); }
            spin_until(t0);
            mbar_wait(BAR(kc < 7 ? BAR_RG1 + kc : BAR_A7), 1);
            if (kc < CE1) mbar_wait(BAR(BAR_RD + kc / 3), 0);
            cload(kc);
            t0 = clock32() + (mbar_test(BAR(BAR_ABOK), 1) ? CLD_DT : CE1_DT);
          }
        }
        float s0 = 0.f, q0 = 0.f, s1 = 0.f, q1 = 0.f;
        const int lr = p * 16 + (lane >> 1);
        const uint32_t src = sb + OFF_A + lr * 128 + ((((lane & 1) * 4) ^ (lr & 7)) << 4);
#pragma unroll 1
        for (int k = 0; k < 9; k++) {
          if (k == 3) {
            mbar_wait(BAR(BAR_SENT), layer);
            if (lane == 0) { cnt_arrive(CNT_X + (layer * 2 * 16 + r) * 9 + 7); }
            __syncwarp();
          }
          if (k == 3) {
            if (layer == 0) cnt_wait(CNT_CS, ep1 * NHELP);
            float4 cs[5];
#pragma unroll
            for (int i = 0; i < 5; i++) cs[i] = __ldcg(reinterpret_cast<const float4*>(g_cs1 + p * 576) + min(lane + i * 32, 143));
#pragma unroll
            for (int i = 0; i < 5; i++) reinterpret_cast<float4*>(smem + OFF_CS1)[min(lane + i * 32, 143) + min(lane + i * 32, 143) / 36] = cs[i];
            __syncwarp();
            mbar_arrive_if(BAR(BAR_CSOK), lane == 0);
          }
          mbar_wait(BAR(BAR_X1F + k), layer);
          uint4 v[4];
#pragma unroll
          for (int i = 0; i < 4; i++) v[i] = lds128((src ^ (i << 4)) + k * A_SLOT);
          sum8(v[0], s0, q0); sum8(v[1], s1, q1); sum8(v[2], s0, q0); sum8(v[3], s1, q1);
        }
        s0 += s1; q0 += q1;
        s0 += __shfl_xor_sync(0xffffffffu, s0, 1);
        q0 += __shfl_xor_sync(0xffffffffu, q0, 1);
        mbar_arrive_if(BAR(BAR_XRD), lane == 0);
        if (!(lane & 1)) stat_publish(&g_stat[(layer + 1) * SEQ + myrow], s0, q0, ep1);
        __syncwarp();
        stat_gather(&g_stat[(layer + 1) * SEQ + r * 128 + lane], ep1, reinterpret_cast<float*>(smem + OFF_RS) + frag_pos(lane), nullptr,
                    reinterpret_cast<float*>(smem + OFF_RS2) + ((lane >> 1) & 3) * 36 + (lane >> 3) * 2 + (lane & 1));
        __syncwarp();
        mbar_arrive_if(BAR(BAR_RSOK), lane == 0);
        if (layer == 0) {
          t0 = clock32();
#pragma unroll 1
          for (int i = 0; i < 32; i++) {
            pace(t0, i * CPF2_DT);
            asm volatile("prefetch.global.L2::evict_normal [%0];" ::"l"(cbase + (size_t)(i & 7) * 16 * SEQ * 2 + (i >> 3) * 256));
          }
        }
      }
    }
  } else {
    asm volatile("setmaxnreg.inc.sync.aligned.u32 232;");
    const uint32_t elect = (tid & 127) == 0;
    const uint32_t lane0 = lane == 0;
    if (wg == 1) {
      const int t = tid & 127;
      const int myrow = r * 128 + p * 16 + (t >> 3);
      const uint4* src = reinterpret_cast<const uint4*>(xin + (size_t)myrow * DM) + (t & 7);
      uint4* dst = reinterpret_cast<uint4*>(xout + (size_t)myrow * DM) + (t & 7);
      const int n = r * 9 + min(t >> 3, 8);
      const uint4* dsrc = reinterpret_cast<const uint4*>((m ? dim : dre) + (size_t)((n / 48) * 192 + q * 48 + n % 48) * DM) + (t & 7);
      float s = 0.f, qq = 0.f, sd = 0.f, s2 = 0.f, q2 = 0.f;
      uint4 v[3], d[3], vn[6], dn[6];
#pragma unroll
      for (int i = 0; i < 3; i++) { v[i] = __ldg(src + i * 8); d[i] = __ldg(dsrc + i * 8); }
#pragma unroll
      for (int i = 0; i < 6; i++) { vn[i] = __ldg(src + 24 + i * 8); dn[i] = __ldg(dsrc + 24 + i * 8); }
      START_SYNC();
#pragma unroll 1
      for (int it = 0; it < 72; it += 24) {
        sum8(v[0], s, qq); sum8(v[1], s2, q2); sum8(v[2], s, qq);
#pragma unroll
        for (int i = 0; i < 3; i++) {
          sd += ((bf_lo(d[i].x) + bf_hi(d[i].x)) + (bf_lo(d[i].y) + bf_hi(d[i].y))) + ((bf_lo(d[i].z) + bf_hi(d[i].z)) + (bf_lo(d[i].w) + bf_hi(d[i].w)));
          dst[it + i * 8] = v[i];
          v[i] = vn[i]; d[i] = dn[i]; vn[i] = vn[i + 3]; dn[i] = dn[i + 3];
        }
      }
      s += s2; qq += q2;
#pragma unroll
      for (int o = 1; o < 8; o <<= 1) {
        s += __shfl_xor_sync(0xffffffffu, s, o);
        qq += __shfl_xor_sync(0xffffffffu, qq, o);
        sd += __shfl_xor_sync(0xffffffffu, sd, o);
      }
      mbar_wait(BAR(BAR_EPOCH), 0);
      const uint32_t ep1 = *reinterpret_cast<volatile uint32_t*>(smem + OFF_EPOCH);
      if ((t & 7) == 0) {
        stat_publish(&g_stat[myrow], s, qq, ep1);
        if (t < 72) asm volatile("st.relaxed.gpu.global.u64 [%0], %1;" ::"l"(&g_csd[p * 144 + n]), "l"(((unsigned long long)ep1 << 32) | __float_as_uint(sd)) : "memory");
      }
      if (t < 32) g_rsum[(t >> 4) * SEQ + r * 128 + p * 16 + (t & 15)] = 0.f;
      __syncwarp();
      if (lane == 0) cnt_arrive(CNT_XINIT + r);
      asm volatile("bar.sync 2, 128;" ::: "memory");
    }

    const int srow = (lane & 7) + ((lane >> 3) & 1) * 8;
    const int schunk = lane >> 4;
    const int frow = warp * 16 + (lane >> 2);
    const uint32_t fpos = (warp * 8 + (lane >> 2)) * 16;
    const uint32_t bfull = BAR(BAR_BFULL);
    const uint32_t bempty = map_rank(BAR(BAR_BEMPTY), lane & 1);
    const uint32_t elect2 = (tid & 127) < 2;
    constexpr uint32_t alo0 = ((sbd + OFF_A) >> 4) | (1u << 16);

#pragma unroll 1
    for (int it = -wg; it < 2; it++) {
      const int layer = max(it, 0);
      const uint32_t live = it >= 0;
      float4 rsf = make_float4(0.f, 0.f, 0.f, 0.f);
      auto rowsums = [&](float (&rsum)[4]) {
#pragma unroll
        for (int i = 0; i < 4; i++) {
          rsum[i] += __shfl_xor_sync(0xffffffffu, rsum[i], 1);
          rsum[i] += __shfl_xor_sync(0xffffffffu, rsum[i], 2);
        }
        const int i = lane & 3;
        const float v = i == 0 ? rsum[0] : (i == 1 ? rsum[1] : (i == 2 ? rsum[2] : rsum[3]));
        asm volatile("red.global.add.f32 [%0], %1;" ::"l"(&g_rsum[layer * SEQ + r * 128 + warp * 32 + lane]), "f"(v) : "memory");
      };
      auto flush = [&](auto& acc0, auto& acc1, auto na, int pi, int atom0) {
        constexpr int NA = decltype(na)::value;
        const int ffn = pi >= 7;
        const uint32_t fdone = BAR(BAR_FDONE + ffn * 9 + atom0);
        mbar_wait(BAR(BAR_FOK + ffn), layer);
        if (atom0) mbar_wait(fdone - 8, layer);
        else if (NA == 3) mbar_wait(BAR(BAR_A8), layer);
        const uint32_t stg = sb + (NA == 3 ? OFF_A + 8 * A_SLOT : OFF_STG) + warp * 4096;
        const uint32_t sad = stg + srow * 128;
        const uint32_t dt = NA == 3 ? (pi == 1 ? FLUSH_DT_A : FLUSH_DT) : (pi == 10 ? FLUSH_DT_D : (pi == 9 ? FLUSH_DT_E : FLUSH_DT4));
        float rs[4];
        if (NA == 3) {
#pragma unroll
          for (int i = 0; i < 4; i++) rs[i] = 0.f;
        } else {
          rs[0] = rsf.x; rs[1] = rsf.y; rs[2] = rsf.z; rs[3] = rsf.w;
        }
        uint32_t tn = clock32() + warp * (dt / 4);
#pragma unroll
        for (int n = 0; n < 2 * NA; n++) {
          const int at = NA == 3 ? n >> 1 : n & 1, hf = NA == 3 ? n & 1 : n >> 1;
          uint32_t w[16];
#pragma unroll
          for (int j = 0; j < 16; j++) {
            const int o = at * 32 + j * 2;
            if (NA == 3) {
              w[j] = (n & 1) ? pk(acc1[o], acc1[o + 1]) : pk(acc0[o], acc0[o + 1]);
              rs[(n & 1) * 2 + (j & 1)] += (n & 1) ? acc1[o] + acc1[o + 1] : acc0[o] + acc0[o + 1];
            } else {
              const float f = rs[hf * 2 + (j & 1)];
              w[j] = hf ? pk(acc1[o] * f, acc1[o + 1] * f) : pk(acc0[o] * f, acc0[o + 1] * f);
            }
          }
#pragma unroll
          for (int j = 0; j < 4; j++)
            stsm4(sad + (n & 1) * 2048 + (((j * 2 + schunk) ^ (srow & 7)) << 4), w[j * 4], w[j * 4 + 1], w[j * 4 + 2], w[j * 4 + 3]);
          if (NA == 3 && n == 5) rowsums(rs);
          fence_async_smem();
          if (n) tn += dt;
          spin_until(tn);
          __syncwarp();
          if (elect_one()) {
            if (!(NA == 2 && n >= 2 && pi == 10 && layer == 0))
              tma_red2d(&maps.xred, stg + (n & 1) * 2048, (atom0 + at) * 64, r * 128 + hf * 64 + warp * 16);
            bulk_commit();
            if (n == 2 * NA - 1) {
              bulk_wait0();
              mbar_arrive(fdone + 8 * (NA - 1));
            } else if (n) {
              asm volatile("cp.async.bulk.wait_group 1;" ::: "memory");
              if (!(n & 1)) mbar_arrive(fdone + 8 * ((n >> 1) - 1));
            }
          }
          __syncwarp();
        }
      };
      if (wg == 0) {
        float acc0[72], acc1[72];
        if (layer == 0) { START_SYNC(); }
        constexpr uint32_t blo0 = (sbd >> 4) | (1u << 16);
        uint32_t ready = 0;
        auto step = [&](int s, auto first) {
          constexpr bool F = decltype(first)::value;
          if (!ready) {
            mbar_wait(BAR(BAR_XF + s), layer);
            mbar_wait(BAR(BAR_DF + s), layer);
            if (F && layer) mbar_wait(BAR(BAR_GO + 15), 0);
          }
          const uint32_t alo = alo0 + s * (A_SLOT >> 4);
          const uint32_t blo = blo0 + (doff(layer, s) >> 4);
          wg_fence();
#pragma unroll
          for (int k = 0; k < 4; k++) {
            if (F && k == 0) {
              wgmma_n144<0, true>(acc0, desc(alo, DESC_HI_128), desc(blo, DESC_HI_128));
              wgmma_n144<0, true>(acc1, desc(alo + 512, DESC_HI_128), desc(blo, DESC_HI_128));
            } else {
              wgmma_n144<0, false>(acc0, desc(alo + k * 2, DESC_HI_128), desc(blo + k * 2, DESC_HI_128));
              wgmma_n144<0, false>(acc1, desc(alo + 512 + k * 2, DESC_HI_128), desc(blo + k * 2, DESC_HI_128));
            }
          }
          wg_commit();
          ready = mbar_test(BAR(BAR_XF + s + 1), layer) & mbar_test(BAR(BAR_DF + min(s + 1, 8)), layer);
          if (!F) {
            wg_wait<1>();
            mbar_arrive_cl_if(bempty + 8 * (BAR_DREL - BAR_BEMPTY - 1 + s), elect2);
            mbar_arrive_if(BAR(BAR_RG1 - 1 + s), elect);
          }
        };
        step(0, TrueT{});
#pragma unroll 1
        for (int s = 1; s < 6; s++) step(s, FalseT{});
        mbar_wait(BAR(BAR_CSD), 0);
        float2 cd[18];
#pragma unroll
        for (int i = 0; i < 9; i++) {
          const float4 t = lds128f(sb + OFF_CSD + (lane & 3) * 144 + i * 16);
          cd[i * 2] = make_float2(t.x, t.y); cd[i * 2 + 1] = make_float2(t.z, t.w);
        }
        const float sg = m ? -1.f : 1.f;
        float2 st[4];
        auto val = [&](const float (&acc)[72], int b, int h, const float2& sv) {
          return pk(fmaf(cd[b].x, sv.y, acc[b * 4 + h * 2]) * sv.x, fmaf(cd[b].y, sv.y, acc[b * 4 + h * 2 + 1]) * sv.x);
        };
        auto tail = [&](float (&acc)[72], auto half) {
          constexpr int H = decltype(half)::value;
#pragma unroll 1
          for (int s = 6; s < 9; s++) {
            if (H == 0) { mbar_wait(BAR(BAR_DF + s), layer); mbar_wait(BAR(BAR_XF + s), layer); }
            else if (layer) mbar_wait(BAR(BAR_XFY - 6 + s), 0);
            const uint32_t alo = alo0 + s * (A_SLOT >> 4) + H * 512;
            const uint32_t blo = blo0 + (doff(layer, s) >> 4);
            wg_fence();
#pragma unroll
            for (int k = 0; k < 4; k++) wgmma_n144<0, false>(acc, desc(alo + k * 2, DESC_HI_128), desc(blo + k * 2, DESC_HI_128));
            wg_commit();
          }
          mbar_wait(BAR(H ? BAR_STATY : BAR_STAT), layer);
          const float2 a = lds64f(sb + OFF_RS + fpos + H * 8), b = lds64f(sb + OFF_MEAN + fpos + H * 8);
          st[H * 2] = make_float2(a.x * sg, b.x); st[H * 2 + 1] = make_float2(a.y * sg, b.y);
          wg_wait<0>();
          reg_fence(acc);
          const bool odd = lane & 1;
          __nv_bfloat16* gp = g_ab + (size_t)((layer * 2 + m) * SEQ + r * 128 + H * 64 + frow) * DM + q * 48 + (lane & 1) * 8 + (lane & 2) * 2;
#pragma unroll
          for (int i = 0; i < 2; i++) {
#pragma unroll
            for (int b = 0; b < 6; b += 2) {
              const uint32_t va = val(acc, b, i, st[H * 2 + i]), vb = val(acc, b + 1, i, st[H * 2 + i]);
              const uint32_t o = __shfl_xor_sync(0xffffffffu, odd ? va : vb, 1);
              asm volatile("st.global.v2.u32 [%0], {%1, %2};" ::"l"(gp + i * 8 * DM + b * 8), "r"(odd ? o : va), "r"(odd ? vb : o) : "memory");
            }
          }
          __syncwarp();
          mbar_arrive_if(BAR(BAR_ABH + H), lane0);
        };
        tail(acc0, IntT<0>{});
        mbar_arrive_if(BAR(BAR_RG1 + 5), elect);
        tail(acc1, IntT<1>{});
        mbar_arrive_if(BAR(BAR_GO), elect);
#pragma unroll
        for (int i = 0; i < NB + 1; i++) mbar_arrive_cl_if(bempty + 8 * i, elect2 && i + layer < NB + 1);
        mbar_arrive_cl_if(bempty + 8 * (BAR_STG2 - BAR_BEMPTY), elect2);
#pragma unroll
        for (int i = 6; i < 9; i++) mbar_arrive_if(BAR(BAR_RG1 + i), elect);
        asm volatile("bar.sync %0, 128;" ::"r"(1 + wg) : "memory");
        const uint32_t stg = sb + OFF_A + 6 * A_SLOT + (warp * 16 + srow) * 96 + schunk * 16;
#pragma unroll
        for (int b2 = 3; b2 < 9; b2++) {
          const uint32_t ad = stg + (b2 / 3) * A_SLOT + (b2 % 3) * 32;
          stsm4(ad, val(acc0, b2 * 2, 0, st[0]), val(acc0, b2 * 2, 1, st[1]), val(acc0, b2 * 2 + 1, 0, st[0]), val(acc0, b2 * 2 + 1, 1, st[1]));
          stsm4(ad + 64 * 96, val(acc1, b2 * 2, 0, st[2]), val(acc1, b2 * 2, 1, st[3]), val(acc1, b2 * 2 + 1, 0, st[2]), val(acc1, b2 * 2 + 1, 1, st[3]));
        }
        fence_async_smem();
        __syncwarp();
        mbar_arrive_if(BAR(BAR_ABSTG), lane0);
      }
#pragma unroll 1
      for (int pi = live ? 2 - wg : 7; pi < 7; pi += 2) {
        {
          float acc0[96], acc1[96];
          int atom0;
          int seq, nt, nt2 = 0, nt3 = 0, gap = 0, gap2 = 0, fbar, rbar = BAR_RNONE, sgm = pi;
          if (pi < 4) { atom0 = (pi - 1) * 3; nt = 8; seq = pi * 16 - 16; fbar = BAR_CF; if (pi == 3) rbar = BAR_RG2; }
          else if (pi == 4) { atom0 = 0; seq = 48; nt = G3A_C1 / 2; nt2 = (G3A_C2 - G3A_C1) / 2; nt3 = 9 - G3A_C2 / 2; gap = G3B_C1; gap2 = G3B_C2 - G3B_C1; fbar = BAR_X1F; }
          else if (pi == 5) { atom0 = 3; seq = 48 + G3A_C1; nt = G3B_C1 / 2; nt2 = (G3B_C2 - G3B_C1) / 2; nt3 = 9 - G3B_C2 / 2; gap = G3A_C2 - G3A_C1; gap2 = 18 - G3A_C2; fbar = BAR_X1F; rbar = BAR_RG3B; }
          else { atom0 = 6; seq = 84; nt = 9; fbar = BAR_X1F + 3; rbar = BAR_RG3C; sgm = 10; }
          constexpr uint32_t blo0 = ((sbd + OFF_B) >> 4) | ((4096u >> 4) << 16);
          uint32_t so = (seq % (NB + 1)) * 8, ph = seq / (NB + 1) + 1 - layer;
          uint32_t alo = alo0 + ((pi == 6) ? 6 * (A_SLOT >> 4) : 0);
          uint32_t fa = BAR(fbar), ra = BAR(rbar), go = BAR(BAR_GO + sgm);
          uint32_t pso, rel, epok = 0;
          auto issue = [&](uint32_t a, auto first) {
            constexpr bool F = decltype(first)::value;
            const uint32_t blo = blo0 + so * (B_SLOT >> 7);
            wg_fence();
            wgmma_n192<1, F>(acc0, desc(a, DESC_HI_128), desc(blo, DESC_HI_128));
            wgmma_n192<1, F>(acc1, desc(a + 512, DESC_HI_128), desc(blo, DESC_HI_128));
            wgmma_n192<1, false>(acc0, desc(a + 2, DESC_HI_128), desc(blo + 128, DESC_HI_128));
            wgmma_n192<1, false>(acc1, desc(a + 514, DESC_HI_128), desc(blo + 128, DESC_HI_128));
            wg_commit();
          };
          auto advance = [&]() { so += 8; if (so == (NB + 1) * 8) { so = 0; ph++; } };
          auto enter = [&]() {
            const uint32_t t0 = mbar_test(fa, layer), t1 = mbar_test(go - 8, layer), t2 = mbar_test(bfull + so, ph);
            if (!(t0 & t1 & t2)) {
              mbar_wait(fa, layer);
              mbar_wait(go - 8, layer);
              mbar_wait(bfull + so, ph);
            }
          };
          enter();
          issue(alo, TrueT{});
          pso = so;
          advance();
          mbar_wait(bfull + so, ph);
#pragma unroll 1
          for (;;) {
            issue(alo + 4, FalseT{});
            const uint32_t cso = so;
            advance();
            alo += A_SLOT >> 4;
            if (alo == alo0 + 9 * (A_SLOT >> 4)) alo = alo0 + 3 * (A_SLOT >> 4);
            fa += 8;
            if (--nt == 0) {
              mbar_arrive_if(go, elect);
              wg_wait<1>();
              mbar_arrive_cl_if(bempty + pso, elect2);
              if (nt2 == 0 && pi >= 4) {
                const uint32_t t0 = mbar_test(BAR(BAR_STAT + 1), layer), t1 = mbar_test(BAR(BAR_CSOK), layer), t2 = mbar_test(BAR(BAR_RG3B + 2), layer);
                epok = t0 & t1 & t2;
              }
              wg_wait<0>();
              mbar_arrive_cl_if(bempty + cso, elect2);
              mbar_arrive_if(ra, elect);
              if (nt2 == 0) break;
              nt = nt2; nt2 = nt3; nt3 = 0;
              const uint32_t t = so + gap * 8;
              so = t % ((NB + 1) * 8); ph += t / ((NB + 1) * 8);
              gap = gap2;
              go += 16;
              rel = 0;
              enter();
            } else {
              const uint32_t ready = mbar_test(fa, layer) & mbar_test(bfull + so, ph);
              wg_wait<1>();
              mbar_arrive_cl_if(bempty + pso, elect2);
              rel = 1;
              if (!ready) {
                mbar_wait(fa, layer);
                mbar_wait(bfull + so, ph);
              }
            }
            issue(alo, FalseT{});
            pso = so;
            advance();
            const uint32_t ready = mbar_test(bfull + so, ph);
            wg_wait<1>();
            mbar_arrive_cl_if(bempty + cso, rel && elect2);
            mbar_arrive_if(ra, rel && elect);
            ra += 8;
            if (!ready) {
              mbar_wait(bfull + so, ph);
            }
          }
        wg_wait<0>();
        reg_fence(acc0); reg_fence(acc1);
        if (pi >= 4 && pi <= 6) {
          if (!epok) {
            mbar_wait(BAR(BAR_STAT + 1), layer);
            mbar_wait(BAR(BAR_CSOK), layer);
            mbar_wait(BAR(BAR_RG3B + 2), layer);
          }
          if (pi == 5) mbar_wait(BAR(BAR_XRD), layer);
          if (pi == 6) asm volatile("bar.sync %0, 128;" ::"r"(1 + wg) : "memory");
          float2 st[4];
          {
            const float4 b = lds128f(sb + OFF_MEAN + fpos);
            st[0].y = b.x; st[1].y = b.y; st[2].y = b.z; st[3].y = b.w;
          }
          const uint32_t cs = sb + OFF_CS1 + (lane & 3) * 592 + atom0 * 64;
          const uint32_t dst = sb + OFF_A + atom0 * A_SLOT + (warp * 16 + srow) * 128;
          float4 cn[2];
          cn[0] = lds128f(cs); cn[1] = lds128f(cs + 16);
#pragma unroll
          for (int b2 = 0; b2 < 12; b2++) {
            if ((b2 & 3) == 0 && pi == 5) mbar_wait(BAR(BAR_RG3C + 3 + (b2 >> 2)), layer);
            const float2 c0 = make_float2(cn[b2 & 1].x, cn[b2 & 1].y), c1 = make_float2(cn[b2 & 1].z, cn[b2 & 1].w);
            if (b2 + 2 < 12) cn[b2 & 1] = lds128f(cs + (b2 + 2) * 16);
            const uint32_t ad = dst + (b2 >> 2) * A_SLOT + ((((b2 & 3) * 2 + schunk) ^ (srow & 7)) << 4);
            const int o = b2 * 8;
            stsm4(ad,
                  pk_relu(fmaf(c0.x, st[0].y, acc0[o]), fmaf(c0.y, st[0].y, acc0[o + 1])),
                  pk_relu(fmaf(c0.x, st[1].y, acc0[o + 2]), fmaf(c0.y, st[1].y, acc0[o + 3])),
                  pk_relu(fmaf(c1.x, st[0].y, acc0[o + 4]), fmaf(c1.y, st[0].y, acc0[o + 5])),
                  pk_relu(fmaf(c1.x, st[1].y, acc0[o + 6]), fmaf(c1.y, st[1].y, acc0[o + 7])));
            stsm4(ad + 8192,
                  pk_relu(fmaf(c0.x, st[2].y, acc1[o]), fmaf(c0.y, st[2].y, acc1[o + 1])),
                  pk_relu(fmaf(c0.x, st[3].y, acc1[o + 2]), fmaf(c0.y, st[3].y, acc1[o + 3])),
                  pk_relu(fmaf(c1.x, st[2].y, acc1[o + 4]), fmaf(c1.y, st[2].y, acc1[o + 5])),
                  pk_relu(fmaf(c1.x, st[3].y, acc1[o + 6]), fmaf(c1.y, st[3].y, acc1[o + 7])));
            if ((b2 & 3) == 3 && (pi == 6 || b2 == 11)) {
              fence_async_smem();
              __syncwarp();
              mbar_arrive_if(BAR(BAR_HF + atom0 + (b2 >> 2)), lane0);
              if (b2 == 11 && pi != 6) { mbar_arrive_if(BAR(BAR_HF + atom0), lane0); mbar_arrive_if(BAR(BAR_HF + atom0 + 1), lane0); }
            }
          }
        } else if (pi == 3) {
          asm volatile("bar.sync %0, 128;" ::"r"(1 + wg) : "memory");
          const uint32_t dst = sb + OFF_A + 6 * A_SLOT + (warp * 16 + srow) * 128;
          float rs[4] = {0.f, 0.f, 0.f, 0.f};
#pragma unroll
          for (int b2 = 0; b2 < 12; b2++) {
            if (b2 == 8) mbar_wait(BAR(BAR_FDONE + 5), layer);
            const uint32_t ad = dst + (b2 >> 2) * A_SLOT + ((((b2 & 3) * 2 + schunk) ^ (srow & 7)) << 4);
            const int o = b2 * 8;
            stsm4(ad, pk(acc0[o], acc0[o + 1]), pk(acc0[o + 2], acc0[o + 3]), pk(acc0[o + 4], acc0[o + 5]), pk(acc0[o + 6], acc0[o + 7]));
            stsm4(ad + 8192, pk(acc1[o], acc1[o + 1]), pk(acc1[o + 2], acc1[o + 3]), pk(acc1[o + 4], acc1[o + 5]), pk(acc1[o + 6], acc1[o + 7]));
            rs[0] += (acc0[o] + acc0[o + 1]) + (acc0[o + 4] + acc0[o + 5]);
            rs[1] += (acc0[o + 2] + acc0[o + 3]) + (acc0[o + 6] + acc0[o + 7]);
            rs[2] += (acc1[o] + acc1[o + 1]) + (acc1[o + 4] + acc1[o + 5]);
            rs[3] += (acc1[o + 2] + acc1[o + 3]) + (acc1[o + 6] + acc1[o + 7]);
            if ((b2 & 3) == 3) {
              fence_async_smem();
              __syncwarp();
              if (b2 == 3) {
                if (lane0) {
                  tma_red2d(&maps.xred, sb + OFF_A + 6 * A_SLOT + warp * 2048, 384, r * 128 + warp * 16);
                  tma_red2d(&maps.xred, sb + OFF_A + 6 * A_SLOT + 8192 + warp * 2048, 384, r * 128 + 64 + warp * 16);
                  bulk_commit();
                }
              } else {
                mbar_arrive_if(BAR(BAR_FDONE + 6 + (b2 >> 2)), lane0);
              }
            }
          }
          rowsums(rs);
          bulk_wait0();
          __syncwarp();
          mbar_arrive_if(BAR(BAR_FDONE + 6), lane0);
        } else {
          flush(acc0, acc1, IntT<3>{}, pi, atom0);
        }
        }
      }
      float2 rsv[16];
      if (live) mbar_wait(BAR(BAR_RSOK), layer);
      rsf = lds128f(sb + OFF_RS + fpos);
      if (wg) {
#pragma unroll
        for (int i = 0; i < 8; i++) {
          const uint4 t = lds128(sb + OFF_RS2 + (lane & 3) * 144 + i * 16);
          rsv[i * 2] = make_float2(__uint_as_float(t.x), __uint_as_float(t.y));
          rsv[i * 2 + 1] = make_float2(__uint_as_float(t.z), __uint_as_float(t.w));
        }
      } else {
#pragma unroll
        for (int i = 0; i < 16; i++) rsv[i] = make_float2(0.f, 0.f);
      }
#pragma unroll 1
      for (int pi = live ? 8 - wg : 11; pi < 12; pi += 2) {
        {
          const int seq = (pi - 7) * 12 + 1;
          uint32_t so = (seq % NB) * 8, ph = seq / NB + layer, pso = 0, cso;
          const uint32_t go = BAR(BAR_GO + 4 + pi);
          auto enter = [&]() {
            const uint32_t t0 = mbar_test(BAR(BAR_HF), layer), t1 = mbar_test(go - 8, layer), t2 = mbar_test(bfull + so, ph);
            if (!(t0 & t1 & t2)) {
              mbar_wait(BAR(BAR_HF), layer);
              mbar_wait(go - 8, layer);
              mbar_wait(bfull + so, ph);
            }
          };
          auto advance = [&]() { cso = so; so += 8; if (so == NB * 8) { so = 0; ph++; } };
          if (pi < 11) {
            float a0[64], a1[64];
            constexpr uint32_t blo0 = ((sbd + OFF_B) >> 4) | ((6144u >> 4) << 16);
            uint32_t alo = alo0, hf = BAR(BAR_HF);
            auto issue = [&](auto jj, auto first) {
              constexpr int J = decltype(jj)::value;
              constexpr bool F = decltype(first)::value;
              const uint32_t blo = blo0 + so * (B_SLOT >> 7);
              wg_fence();
#pragma unroll
              for (int j = 0; j < 3; j++) {
                const int u = J * 3 + j;
                const uint64_t da0 = desc(alo + (u >> 2) * (A_SLOT >> 4) + (u & 3) * 2, DESC_HI_128);
                const uint64_t da1 = desc(alo + (u >> 2) * (A_SLOT >> 4) + (u & 3) * 2 + 512, DESC_HI_128);
                const uint64_t db = desc(blo + j * 128, DESC_HI_128);
                if (F && j == 0) { wgmma_n128<1, true>(a0, da0, db); wgmma_n128<1, true>(a1, da1, db); }
                else { wgmma_n128<1, false>(a0, da0, db); wgmma_n128<1, false>(a1, da1, db); }
              }
              wg_commit();
              advance();
            };
            auto next = [&](int tile, auto first) {
              uint32_t ready = mbar_test(bfull + so, ph);
              if (tile >= 0) ready &= mbar_test(hf + 8 * tile, layer);
              if (!decltype(first)::value) {
                wg_wait<1>();
                mbar_arrive_cl_if(bempty + pso, elect2);
              }
              pso = cso;
              if (!ready) {
                if (tile >= 0) mbar_wait(hf + 8 * tile, layer);
                mbar_wait(bfull + so, ph);
              }
            };
            enter();
            issue(IntT<0>{}, TrueT{});
            next(1, TrueT{});
#pragma unroll 1
            for (;;) {
              issue(IntT<1>{}, FalseT{});
              next(2, FalseT{});
              issue(IntT<2>{}, FalseT{});
              next(-1, FalseT{});
              issue(IntT<3>{}, FalseT{});
              if (alo == alo0 + 6 * (A_SLOT >> 4)) break;
              alo += 3 * (A_SLOT >> 4);
              hf += 24;
              next(0, FalseT{});
              issue(IntT<0>{}, FalseT{});
              next(1, FalseT{});
            }
            mbar_arrive_if(go, elect);
            wg_wait<1>();
            mbar_arrive_cl_if(bempty + pso, elect2);
            wg_wait<0>();
            mbar_arrive_cl_if(bempty + cso, elect2);
            reg_fence(a0); reg_fence(a1);
            flush(a0, a1, IntT<2>{}, pi, (pi - 7) * 2);
          } else {
            float a0[64];
            const uint32_t el = elect & live, el2 = elect2 & live;
            auto step = [&](int s, auto first) {
              constexpr bool F = decltype(first)::value;
              const uint32_t blo = (((sbd + OFF_B) >> 4) | (1u << 16)) + so * (B_SLOT >> 7);
              wg_fence();
#pragma unroll
              for (int j = 0; j < 6; j++) {
                const int u = s * 6 + j;
                const uint64_t dh = desc(alo0 + (u >> 2) * (A_SLOT >> 4) + (u & 3) * 2, DESC_HI_128);
                if (F && j == 0) wgmma_n128<0, true, 1>(a0, desc(blo, DESC_HI_128), dh);
                else wgmma_n128<0, false, 1>(a0, desc(blo + j * 128, DESC_HI_128), dh);
              }
              wg_commit();
              advance();
              mbar_arrive_if(go, el && s == 5);
              const uint32_t ready = mbar_test(bfull + so, ph) | (s == 5) | !live;
              if (!F) {
                wg_wait<1>();
                mbar_arrive_cl_if(bempty + pso, el2);
                mbar_arrive_if(BAR(BAR_RG4 - 1 + ((6 * s) >> 2)), el);
                mbar_arrive_if(BAR(BAR_RG4 - 2 + ((6 * s) >> 2)), el && !(s & 1));
              }
              pso = cso;
              if (!ready) mbar_wait(bfull + so, ph);
            };
            if (live) enter();
            step(0, TrueT{});
#pragma unroll 1
            for (int s = live ? 1 : 5; s < 6; s++) step(s, FalseT{});
            wg_wait<0>();
            mbar_arrive_cl_if(bempty + pso, el2);
            mbar_arrive_if(BAR(BAR_RG4 + 7), el);
            mbar_arrive_if(BAR(BAR_RG4 + 8), el);
            reg_fence(a0);
            {
              asm volatile("bar.sync %0, 128;" ::"r"(1 + wg) : "memory");
              const uint32_t tb = sb + OFF_A + 8 * A_SLOT;
              const uint32_t ad = tb + ((lane >> 4) * 8 + (lane & 7)) * 128 + (((warp * 2 + ((lane >> 3) & 1)) ^ (lane & 7)) << 4);
#pragma unroll
              for (int b2 = 0; b2 < 8; b2++) {
                const float2 f0 = rsv[b2 * 2], f1 = rsv[b2 * 2 + 1];
                const int o = b2 * 8;
                asm volatile("{\n.reg .pred p;\nsetp.ne.u32 p, %5, 0;\n@p stmatrix.sync.aligned.m8n8.x4.trans.shared.b16 [%0], {%1,%2,%3,%4};\n}" ::"r"(ad + b2 * 2048),
                             "r"(pk(a0[o] * f0.x, a0[o + 1] * f0.y)), "r"(pk(a0[o + 2] * f0.x, a0[o + 3] * f0.y)),
                             "r"(pk(a0[o + 4] * f1.x, a0[o + 5] * f1.y)), "r"(pk(a0[o + 6] * f1.x, a0[o + 7] * f1.y)), "r"(live));
              }
              fence_async_smem();
              __syncwarp();
              mbar_arrive_if(BAR(BAR_FDONE + 17), lane0 & live);
              if (it == 0) {
                const int t = tid & 127, row = t >> 1;
                const uint32_t ra = sb + OFF_A + row * 128 + ((t & 15) << 3);
                float s0 = 0.f, q0 = 0.f, s1 = 0.f, q1 = 0.f;
#pragma unroll 1
                for (int j = 0; j < 6; j++) {
                  const int k0 = (j >> 1) * 3, h = j & 1;
                  if (!h || j == 5) {
#pragma unroll 1
                    for (int i = 0; i < 3; i++) mbar_wait(BAR(h ? BAR_XFY + i : BAR_XF + k0 + i), !h);
                  }
                  const uint32_t a = ra + k0 * A_SLOT + h * 8192;
                  uint4 v[12];
#pragma unroll
                  for (int i = 0; i < 12; i++) {
                    asm volatile("ld.shared.v2.u32 {%0,%1}, [%2];" : "=r"(v[i].x), "=r"(v[i].y) : "r"((a ^ ((i & 3) << 5)) + (i >> 2) * A_SLOT) : "memory");
                    asm volatile("ld.shared.v2.u32 {%0,%1}, [%2];" : "=r"(v[i].z), "=r"(v[i].w) : "r"((a ^ (((i & 3) << 5) | 16)) + (i >> 2) * A_SLOT) : "memory");
                  }
                  float s2 = 0.f, q2 = 0.f;
#pragma unroll
                  for (int i = 0; i < 12; i += 2) { sum8(v[i], s0, q0); sum8(v[i + 1], s2, q2); }
                  s0 += s2; q0 += q2;
                  if (j >= 4) {
                    s0 += __shfl_xor_sync(0xffffffffu, s0, 1);
                    q0 += __shfl_xor_sync(0xffffffffu, q0, 1);
                    const float mean = s0 * (1.0f / DM);
                    reinterpret_cast<float*>(smem + ((t & 1) ? OFF_RS : OFF_MEAN))[frag_pos(row + h * 64)] =
                        (t & 1) ? rsqrtf(fmaxf(q0 * (1.0f / DM) - mean * mean, 0.f) + 1e-5f) : -mean;
                  }
                  { float u = s0; s0 = s1; s1 = u; u = q0; q0 = q1; q1 = u; }
                  if (h || j == 4) {
                    asm volatile("bar.sync %0, 128;" ::"r"(1 + wg) : "memory");
                    mbar_arrive_if(BAR(j == 4 ? BAR_STAT : (j == 5 ? BAR_STATY : BAR_RD + (j >> 1))), elect);
                  }
                }
              }
            }
          }
        }
      }
    }
  }
#undef BAR
}

typedef CUresult (*EncodeFn)(CUtensorMap*, CUtensorMapDataType, cuuint32_t, void*, const cuuint64_t*, const cuuint64_t*, const cuuint32_t*,
                             const cuuint32_t*, CUtensorMapInterleave, CUtensorMapSwizzle, CUtensorMapL2promotion, CUtensorMapFloatOOBfill);

void make2d(EncodeFn enc, CUtensorMap* m, const void* ptr, uint64_t inner, uint64_t outer, uint32_t bi, uint32_t bo, CUtensorMapSwizzle sw) {
  cuuint64_t d[2] = {inner, outer};
  cuuint64_t s[1] = {inner * 2};
  cuuint32_t b[2] = {bi, bo}, e[2] = {1, 1};
  enc(m, CU_TENSOR_MAP_DATA_TYPE_BFLOAT16, 2, const_cast<void*>(ptr), d, s, b, e, CU_TENSOR_MAP_INTERLEAVE_NONE, sw,
      CU_TENSOR_MAP_L2_PROMOTION_L2_128B, CU_TENSOR_MAP_FLOAT_OOB_FILL_NONE);
}
void make3d(EncodeFn enc, CUtensorMap* m, const void* ptr, uint64_t d0, uint64_t d1, uint64_t d2, uint64_t s1, uint64_t s2,
            uint32_t b0, uint32_t b1, uint32_t b2, CUtensorMapSwizzle sw) {
  cuuint64_t d[3] = {d0, d1, d2};
  cuuint64_t s[2] = {s1, s2};
  cuuint32_t b[3] = {b0, b1, b2}, e[3] = {1, 1, 1};
  enc(m, CU_TENSOR_MAP_DATA_TYPE_BFLOAT16, 3, const_cast<void*>(ptr), d, s, b, e, CU_TENSOR_MAP_INTERLEAVE_NONE, sw,
      CU_TENSOR_MAP_L2_PROMOTION_L2_128B, CU_TENSOR_MAP_FLOAT_OOB_FILL_NONE);
}

}

extern "C" void kernel_launch(void* const* d_in, const int* in_sizes, int n_in, void* d_out, int out_size) {
  (void)in_sizes; (void)n_in; (void)out_size;
  const __nv_bfloat16* x = (const __nv_bfloat16*)d_in[0];
  const __nv_bfloat16* cr = (const __nv_bfloat16*)d_in[1];
  const __nv_bfloat16* ci = (const __nv_bfloat16*)d_in[2];
  const __nv_bfloat16* dr = (const __nv_bfloat16*)d_in[3];
  const __nv_bfloat16* di = (const __nv_bfloat16*)d_in[4];
  const __nv_bfloat16* w1 = (const __nv_bfloat16*)d_in[6];
  const __nv_bfloat16* w2 = (const __nv_bfloat16*)d_in[7];
  __nv_bfloat16* out = (__nv_bfloat16*)d_out;

  void* fn = nullptr;
  cudaDriverEntryPointQueryResult qr;
  cudaGetDriverEntryPoint("cuTensorMapEncodeTiled", &fn, cudaEnableDefault, &qr);
  EncodeFn enc = (EncodeFn)fn;
  void* ab = nullptr;
  cudaGetSymbolAddress(&ab, g_ab);

  Maps maps;
  make2d(enc, &maps.xin, x, DM, SEQ, 64, 128, CU_TENSOR_MAP_SWIZZLE_128B);
  make2d(enc, &maps.xld, out, DM, SEQ, 64, 128, CU_TENSOR_MAP_SWIZZLE_128B);
  make2d(enc, &maps.xh, out, DM, SEQ, 64, 64, CU_TENSOR_MAP_SWIZZLE_128B);
  make2d(enc, &maps.xred, out, DM, SEQ, 64, 16, CU_TENSOR_MAP_SWIZZLE_128B);
  make2d(enc, &maps.cr, cr, SEQ, SEQ, 64, 128, CU_TENSOR_MAP_SWIZZLE_128B);
  make2d(enc, &maps.ci, ci, SEQ, SEQ, 64, 128, CU_TENSOR_MAP_SWIZZLE_128B);
  make3d(enc, &maps.dr, dr, DM, 192, 3, DM * 2, 192 * DM * 2, 64, 48, 3, CU_TENSOR_MAP_SWIZZLE_128B);
  make3d(enc, &maps.di, di, DM, 192, 3, DM * 2, 192 * DM * 2, 64, 48, 3, CU_TENSOR_MAP_SWIZZLE_128B);
  make3d(enc, &maps.abld, ab, 64, 4 * SEQ, DM / 64, DM * 2, 128, 64, 32, 3, CU_TENSOR_MAP_SWIZZLE_128B);
  make2d(enc, &maps.abst, ab, DM, 4 * SEQ, 48, 128, CU_TENSOR_MAP_SWIZZLE_NONE);
  make3d(enc, &maps.w1, w1, 64, DM, DFF / 64, DFF * 2, 128, 64, 32, 3, CU_TENSOR_MAP_SWIZZLE_128B);
  make3d(enc, &maps.w2, w2, 64, DFF, DM / 64, DM * 2, 128, 64, 48, 2, CU_TENSOR_MAP_SWIZZLE_128B);
  make3d(enc, &maps.w2n, w2, 64, DFF, DM / 64, DM * 2, 128, 64, 96, 1, CU_TENSOR_MAP_SWIZZLE_128B);

  cudaFuncSetAttribute(fnet_ffn_kernel, cudaFuncAttributeMaxDynamicSharedMemorySize, SMEM_BYTES);
  cudaLaunchConfig_t cfg = {};
  cfg.gridDim = dim3(NGRID);
  cfg.blockDim = dim3(384);
  cfg.dynamicSmemBytes = SMEM_BYTES;
  cfg.stream = cudaStreamPerThread;
  cudaLaunchAttribute at[1];
  at[0].id = cudaLaunchAttributeClusterDimension;
  at[0].val.clusterDim.x = 2; at[0].val.clusterDim.y = 1; at[0].val.clusterDim.z = 1;
  cfg.attrs = at;
  cfg.numAttrs = 1;
  cudaLaunchKernelEx(&cfg, fnet_ffn_kernel, maps, x, cr, ci, dr, di, out);
}
```

```cpp
#include <cuda_runtime.h>
#include <cuda_bf16.h>
#include <cuda.h>
#include <stdint.h>

namespace {

constexpr int SEQ = 2048, DM = 576, DFF = 4608;
constexpr int NHELP = 4, NWORK = 128, NGRID = NHELP + NWORK;

constexpr int A_SLOT = 16384, B_SLOT = 12288, NB = 5, D_SLOT = 18432;
constexpr int OFF_A = 0;
constexpr int OFF_B = 9 * A_SLOT;
constexpr int OFF_STG = OFF_B + NB * B_SLOT;
constexpr int OFF_CS1 = OFF_STG + 12288;
constexpr int OFF_CSD = OFF_STG + 16384;
constexpr int OFF_EPOCH = OFF_CSD + 576;
constexpr int OFF_RS = OFF_CSD + 640;
constexpr int OFF_BAR = OFF_RS + 512;
constexpr int SMEM_BYTES = 232448;

constexpr int BAR_HF = 0  , BAR_ABSTG = 9, BAR_FDONE = 11  , BAR_ABH = 29  ,
              BAR_BEMPTY = 34  , BAR_DREL = 40  , BAR_STGF = 45, BAR_STG2 = 46,
              BAR_CF = 51  , BAR_X1F = 59  ,
              BAR_RG1 = 71, BAR_RG2 = 80, BAR_RG3B = 89, BAR_RG3C = 98, BAR_RG4 = 107, BAR_RNONE = 116  ,
              BAR_STAT = 125  , BAR_FOK = 127  , BAR_EPOCH = 129, BAR_CSD = 130, BAR_SENT = 131, BAR_RSOK = 132,
              BAR_CSOK = 133, BAR_A7 = 134, BAR_A8 = 135,
              BAR_XF = 136  , BAR_DF = 145  , BAR_GO = 154  , BAR_XOK = 170  , BAR_RD = 176  ,
              BAR_BFULL = 178  , BAR_AB1 = 184, BAR_XRD = 185, BAR_STATY = 186, BAR_XFY = 187  , BAR_SENTX = 190,
              BAR_SENTY = 191, BAR_ABOK = 192  , NBAR = 204;
constexpr int OFF_MEAN = OFF_BAR + NBAR * 8;
constexpr int OFF_RS2 = OFF_MEAN + 512;
static_assert(OFF_RS2 % 16 == 0 && OFF_RS2 + 576 <= SMEM_BYTES, "smem");

constexpr int CNT_STRIDE = 32;
constexpr int CNT_AB = 0;
constexpr int CNT_X = 256;
constexpr int CNT_XINIT = CNT_X + 432;
constexpr int CNT_G3 = CNT_XINIT + 16;
constexpr int CNT_CS = CNT_G3 + 32;
constexpr int CNT_TICKET = CNT_CS + 1;
constexpr int NCNT = CNT_TICKET + 1;

__device__ uint32_t g_cnt[NCNT * CNT_STRIDE];
__device__ __align__(128) __nv_bfloat16 g_ab[2 * 2 * SEQ * DM];
__device__ __align__(16) float g_cs1[DFF];
__device__ __align__(16) float g_rsum[2 * SEQ];
__device__ __align__(16) unsigned long long g_csd[8 * 144];
__device__ ulonglong2 g_stat[3 * SEQ];

template <int V> struct IntT { static constexpr int value = V; };
struct TrueT { static constexpr bool value = true; };
struct FalseT { static constexpr bool value = false; };

struct Maps {
  CUtensorMap xin, xld, xh, xred, cr, ci, dr, di, abld, abst, w1, w2, w2n;
};

template<int TB, bool FIRST, int TA = 0> __device__ __forceinline__ void wgmma_n128(float (&d)[64], uint64_t da, uint64_t db){
  if (FIRST) {
    asm volatile("wgmma.mma_async.sync.aligned.m64n128k16.f32.bf16.bf16 {%0, %1, %2, %3, %4, %5, %6, %7, %8, %9, %10, %11, %12, %13, %14, %15, %16, %17, %18, %19, %20, %21, %22, %23, %24, %25, %26, %27, %28, %29, %30, %31, %32, %33, %34, %35, %36, %37, %38, %39, %40, %41, %42, %43, %44, %45, %46, %47, %48, %49, %50, %51, %52, %53, %54, %55, %56, %57, %58, %59, %60, %61, %62, %63}, %64, %65, 0, 1, 1, %67, %66;"
     : "=f"(d[0]), "=f"(d[1]), "=f"(d[2]), "=f"(d[3]), "=f"(d[4]), "=f"(d[5]), "=f"(d[6]), "=f"(d[7]), "=f"(d[8]), "=f"(d[9]), "=f"(d[10]), "=f"(d[11]), "=f"(d[12]), "=f"(d[13]), "=f"(d[14]), "=f"(d[15]), "=f"(d[16]), "=f"(d[17]), "=f"(d[18]), "=f"(d[19]), "=f"(d[20]), "=f"(d[21]), "=f"(d[22]), "=f"(d[23]), "=f"(d[24]), "=f"(d[25]), "=f"(d[26]), "=f"(d[27]), "=f"(d[28]), "=f"(d[29]), "=f"(d[30]), "=f"(d[31]), "=f"(d[32]), "=f"(d[33]), "=f"(d[34]), "=f"(d[35]), "=f"(d[36]), "=f"(d[37]), "=f"(d[38]), "=f"(d[39]), "=f"(d[40]), "=f"(d[41]), "=f"(d[42]), "=f"(d[43]), "=f"(d[44]), "=f"(d[45]), "=f"(d[46]), "=f"(d[47]), "=f"(d[48]), "=f"(d[49]), "=f"(d[50]), "=f"(d[51]), "=f"(d[52]), "=f"(d[53]), "=f"(d[54]), "=f"(d[55]), "=f"(d[56]), "=f"(d[57]), "=f"(d[58]), "=f"(d[59]), "=f"(d[60]), "=f"(d[61]), "=f"(d[62]), "=f"(d[63])
     : "l"(da), "l"(db), "n"(TB), "n"(TA));
  } else {
    asm volatile("wgmma.mma_async.sync.aligned.m64n128k16.f32.bf16.bf16 {%0, %1, %2, %3, %4, %5, %6, %7, %8, %9, %10, %11, %12, %13, %14, %15, %16, %17, %18, %19, %20, %21, %22, %23, %24, %25, %26, %27, %28, %29, %30, %31, %32, %33, %34, %35, %36, %37, %38, %39, %40, %41, %42, %43, %44, %45, %46, %47, %48, %49, %50, %51, %52, %53, %54, %55, %56, %57, %58, %59, %60, %61, %62, %63}, %64, %65, 1, 1, 1, %67, %66;"
     : "+f"(d[0]), "+f"(d[1]), "+f"(d[2]), "+f"(d[3]), "+f"(d[4]), "+f"(d[5]), "+f"(d[6]), "+f"(d[7]), "+f"(d[8]), "+f"(d[9]), "+f"(d[10]), "+f"(d[11]), "+f"(d[12]), "+f"(d[13]), "+f"(d[14]), "+f"(d[15]), "+f"(d[16]), "+f"(d[17]), "+f"(d[18]), "+f"(d[19]), "+f"(d[20]), "+f"(d[21]), "+f"(d[22]), "+f"(d[23]), "+f"(d[24]), "+f"(d[25]), "+f"(d[26]), "+f"(d[27]), "+f"(d[28]), "+f"(d[29]), "+f"(d[30]), "+f"(d[31]), "+f"(d[32]), "+f"(d[33]), "+f"(d[34]), "+f"(d[35]), "+f"(d[36]), "+f"(d[37]), "+f"(d[38]), "+f"(d[39]), "+f"(d[40]), "+f"(d[41]), "+f"(d[42]), "+f"(d[43]), "+f"(d[44]), "+f"(d[45]), "+f"(d[46]), "+f"(d[47]), "+f"(d[48]), "+f"(d[49]), "+f"(d[50]), "+f"(d[51]), "+f"(d[52]), "+f"(d[53]), "+f"(d[54]), "+f"(d[55]), "+f"(d[56]), "+f"(d[57]), "+f"(d[58]), "+f"(d[59]), "+f"(d[60]), "+f"(d[61]), "+f"(d[62]), "+f"(d[63])
     : "l"(da), "l"(db), "n"(TB), "n"(TA));
  }
}
template<int TB, bool FIRST, int TA = 0> __device__ __forceinline__ void wgmma_n144(float (&d)[72], uint64_t da, uint64_t db){
  if (FIRST) {
    asm volatile("wgmma.mma_async.sync.aligned.m64n144k16.f32.bf16.bf16 {%0, %1, %2, %3, %4, %5, %6, %7, %8, %9, %10, %11, %12, %13, %14, %15, %16, %17, %18, %19, %20, %21, %22, %23, %24, %25, %26, %27, %28, %29, %30, %31, %32, %33, %34, %35, %36, %37, %38, %39, %40, %41, %42, %43, %44, %45, %46, %47, %48, %49, %50, %51, %52, %53, %54, %55, %56, %57, %58, %59, %60, %61, %62, %63, %64, %65, %66, %67, %68, %69, %70, %71}, %72, %73, 0, 1, 1, %75, %74;"
     : "=f"(d[0]), "=f"(d[1]), "=f"(d[2]), "=f"(d[3]), "=f"(d[4]), "=f"(d[5]), "=f"(d[6]), "=f"(d[7]), "=f"(d[8]), "=f"(d[9]), "=f"(d[10]), "=f"(d[11]), "=f"(d[12]), "=f"(d[13]), "=f"(d[14]), "=f"(d[15]), "=f"(d[16]), "=f"(d[17]), "=f"(d[18]), "=f"(d[19]), "=f"(d[20]), "=f"(d[21]), "=f"(d[22]), "=f"(d[23]), "=f"(d[24]), "=f"(d[25]), "=f"(d[26]), "=f"(d[27]), "=f"(d[28]), "=f"(d[29]), "=f"(d[30]), "=f"(d[31]), "=f"(d[32]), "=f"(d[33]), "=f"(d[34]), "=f"(d[35]), "=f"(d[36]), "=f"(d[37]), "=f"(d[38]), "=f"(d[39]), "=f"(d[40]), "=f"(d[41]), "=f"(d[42]), "=f"(d[43]), "=f"(d[44]), "=f"(d[45]), "=f"(d[46]), "=f"(d[47]), "=f"(d[48]), "=f"(d[49]), "=f"(d[50]), "=f"(d[51]), "=f"(d[52]), "=f"(d[53]), "=f"(d[54]), "=f"(d[55]), "=f"(d[56]), "=f"(d[57]), "=f"(d[58]), "=f"(d[59]), "=f"(d[60]), "=f"(d[61]), "=f"(d[62]), "=f"(d[63]), "=f"(d[64]), "=f"(d[65]), "=f"(d[66]), "=f"(d[67]), "=f"(d[68]), "=f"(d[69]), "=f"(d[70]), "=f"(d[71])
     : "l"(da), "l"(db), "n"(TB), "n"(TA));
  } else {
    asm volatile("wgmma.mma_async.sync.aligned.m64n144k16.f32.bf16.bf16 {%0, %1, %2, %3, %4, %5, %6, %7, %8, %9, %10, %11, %12, %13, %14, %15, %16, %17, %18, %19, %20, %21, %22, %23, %24, %25, %26, %27, %28, %29, %30, %31, %32, %33, %34, %35, %36, %37, %38, %39, %40, %41, %42, %43, %44, %45, %46, %47, %48, %49, %50, %51, %52, %53, %54, %55, %56, %57, %58, %59, %60, %61, %62, %63, %64, %65, %66, %67, %68, %69, %70, %71}, %72, %73, 1, 1, 1, %75, %74;"
     : "+f"(d[0]), "+f"(d[1]), "+f"(d[2]), "+f"(d[3]), "+f"(d[4]), "+f"(d[5]), "+f"(d[6]), "+f"(d[7]), "+f"(d[8]), "+f"(d[9]), "+f"(d[10]), "+f"(d[11]), "+f"(d[12]), "+f"(d[13]), "+f"(d[14]), "+f"(d[15]), "+f"(d[16]), "+f"(d[17]), "+f"(d[18]), "+f"(d[19]), "+f"(d[20]), "+f"(d[21]), "+f"(d[22]), "+f"(d[23]), "+f"(d[24]), "+f"(d[25]), "+f"(d[26]), "+f"(d[27]), "+f"(d[28]), "+f"(d[29]), "+f"(d[30]), "+f"(d[31]), "+f"(d[32]), "+f"(d[33]), "+f"(d[34]), "+f"(d[35]), "+f"(d[36]), "+f"(d[37]), "+f"(d[38]), "+f"(d[39]), "+f"(d[40]), "+f"(d[41]), "+f"(d[42]), "+f"(d[43]), "+f"(d[44]), "+f"(d[45]), "+f"(d[46]), "+f"(d[47]), "+f"(d[48]), "+f"(d[49]), "+f"(d[50]), "+f"(d[51]), "+f"(d[52]), "+f"(d[53]), "+f"(d[54]), "+f"(d[55]), "+f"(d[56]), "+f"(d[57]), "+f"(d[58]), "+f"(d[59]), "+f"(d[60]), "+f"(d[61]), "+f"(d[62]), "+f"(d[63]), "+f"(d[64]), "+f"(d[65]), "+f"(d[66]), "+f"(d[67]), "+f"(d[68]), "+f"(d[69]), "+f"(d[70]), "+f"(d[71])
     : "l"(da), "l"(db), "n"(TB), "n"(TA));
  }
}
template<int TB, bool FIRST, int TA = 0> __device__ __forceinline__ void wgmma_n192(float (&d)[96], uint64_t da, uint64_t db){
  if (FIRST) {
    asm volatile("wgmma.mma_async.sync.aligned.m64n192k16.f32.bf16.bf16 {%0, %1, %2, %3, %4, %5, %6, %7, %8, %9, %10, %11, %12, %13, %14, %15, %16, %17, %18, %19, %20, %21, %22, %23, %24, %25, %26, %27, %28, %29, %30, %31, %32, %33, %34, %35, %36, %37, %38, %39, %40, %41, %42, %43, %44, %45, %46, %47, %48, %49, %50, %51, %52, %53, %54, %55, %56, %57, %58, %59, %60, %61, %62, %63, %64, %65, %66, %67, %68, %69, %70, %71, %72, %73, %74, %75, %76, %77, %78, %79, %80, %81, %82, %83, %84, %85, %86, %87, %88, %89, %90, %91, %92, %93, %94, %95}, %96, %97, 0, 1, 1, %99, %98;"
     : "=f"(d[0]), "=f"(d[1]), "=f"(d[2]), "=f"(d[3]), "=f"(d[4]), "=f"(d[5]), "=f"(d[6]), "=f"(d[7]), "=f"(d[8]), "=f"(d[9]), "=f"(d[10]), "=f"(d[11]), "=f"(d[12]), "=f"(d[13]), "=f"(d[14]), "=f"(d[15]), "=f"(d[16]), "=f"(d[17]), "=f"(d[18]), "=f"(d[19]), "=f"(d[20]), "=f"(d[21]), "=f"(d[22]), "=f"(d[23]), "=f"(d[24]), "=f"(d[25]), "=f"(d[26]), "=f"(d[27]), "=f"(d[28]), "=f"(d[29]), "=f"(d[30]), "=f"(d[31]), "=f"(d[32]), "=f"(d[33]), "=f"(d[34]), "=f"(d[35]), "=f"(d[36]), "=f"(d[37]), "=f"(d[38]), "=f"(d[39]), "=f"(d[40]), "=f"(d[41]), "=f"(d[42]), "=f"(d[43]), "=f"(d[44]), "=f"(d[45]), "=f"(d[46]), "=f"(d[47]), "=f"(d[48]), "=f"(d[49]), "=f"(d[50]), "=f"(d[51]), "=f"(d[52]), "=f"(d[53]), "=f"(d[54]), "=f"(d[55]), "=f"(d[56]), "=f"(d[57]), "=f"(d[58]), "=f"(d[59]), "=f"(d[60]), "=f"(d[61]), "=f"(d[62]), "=f"(d[63]), "=f"(d[64]), "=f"(d[65]), "=f"(d[66]), "=f"(d[67]), "=f"(d[68]), "=f"(d[69]), "=f"(d[70]), "=f"(d[71]), "=f"(d[72]), "=f"(d[73]), "=f"(d[74]), "=f"(d[75]), "=f"(d[76]), "=f"(d[77]), "=f"(d[78]), "=f"(d[79]), "=f"(d[80]), "=f"(d[81]), "=f"(d[82]), "=f"(d[83]), "=f"(d[84]), "=f"(d[85]), "=f"(d[86]), "=f"(d[87]), "=f"(d[88]), "=f"(d[89]), "=f"(d[90]), "=f"(d[91]), "=f"(d[92]), "=f"(d[93]), "=f"(d[94]), "=f"(d[95])
     : "l"(da), "l"(db), "n"(TB), "n"(TA));
  } else {
    asm volatile("wgmma.mma_async.sync.aligned.m64n192k16.f32.bf16.bf16 {%0, %1, %2, %3, %4, %5, %6, %7, %8, %9, %10, %11, %12, %13, %14, %15, %16, %17, %18, %19, %20, %21, %22, %23, %24, %25, %26, %27, %28, %29, %30, %31, %32, %33, %34, %35, %36, %37, %38, %39, %40, %41, %42, %43, %44, %45, %46, %47, %48, %49, %50, %51, %52, %53, %54, %55, %56, %57, %58, %59, %60, %61, %62, %63, %64, %65, %66, %67, %68, %69, %70, %71, %72, %73, %74, %75, %76, %77, %78, %79, %80, %81, %82, %83, %84, %85, %86, %87, %88, %89, %90, %91, %92, %93, %94, %95}, %96, %97, 1, 1, 1, %99, %98;"
     : "+f"(d[0]), "+f"(d[1]), "+f"(d[2]), "+f"(d[3]), "+f"(d[4]), "+f"(d[5]), "+f"(d[6]), "+f"(d[7]), "+f"(d[8]), "+f"(d[9]), "+f"(d[10]), "+f"(d[11]), "+f"(d[12]), "+f"(d[13]), "+f"(d[14]), "+f"(d[15]), "+f"(d[16]), "+f"(d[17]), "+f"(d[18]), "+f"(d[19]), "+f"(d[20]), "+f"(d[21]), "+f"(d[22]), "+f"(d[23]), "+f"(d[24]), "+f"(d[25]), "+f"(d[26]), "+f"(d[27]), "+f"(d[28]), "+f"(d[29]), "+f"(d[30]), "+f"(d[31]), "+f"(d[32]), "+f"(d[33]), "+f"(d[34]), "+f"(d[35]), "+f"(d[36]), "+f"(d[37]), "+f"(d[38]), "+f"(d[39]), "+f"(d[40]), "+f"(d[41]), "+f"(d[42]), "+f"(d[43]), "+f"(d[44]), "+f"(d[45]), "+f"(d[46]), "+f"(d[47]), "+f"(d[48]), "+f"(d[49]), "+f"(d[50]), "+f"(d[51]), "+f"(d[52]), "+f"(d[53]), "+f"(d[54]), "+f"(d[55]), "+f"(d[56]), "+f"(d[57]), "+f"(d[58]), "+f"(d[59]), "+f"(d[60]), "+f"(d[61]), "+f"(d[62]), "+f"(d[63]), "+f"(d[64]), "+f"(d[65]), "+f"(d[66]), "+f"(d[67]), "+f"(d[68]), "+f"(d[69]), "+f"(d[70]), "+f"(d[71]), "+f"(d[72]), "+f"(d[73]), "+f"(d[74]), "+f"(d[75]), "+f"(d[76]), "+f"(d[77]), "+f"(d[78]), "+f"(d[79]), "+f"(d[80]), "+f"(d[81]), "+f"(d[82]), "+f"(d[83]), "+f"(d[84]), "+f"(d[85]), "+f"(d[86]), "+f"(d[87]), "+f"(d[88]), "+f"(d[89]), "+f"(d[90]), "+f"(d[91]), "+f"(d[92]), "+f"(d[93]), "+f"(d[94]), "+f"(d[95])
     : "l"(da), "l"(db), "n"(TB), "n"(TA));
  }
}

__device__ __forceinline__ uint32_t clock32() { uint32_t t; asm volatile("mov.u32 %0, %%clock;" : "=r"(t)); return t; }
__device__ __forceinline__ bool elect_one() {
  uint32_t pred;
  asm volatile("{\n.reg .pred p;\nelect.sync _|p, 0xffffffff;\nselp.u32 %0, 1, 0, p;\n}" : "=r"(pred));
  return pred != 0;
}
__device__ __forceinline__ void mbar_init(uint32_t b, int c) { asm volatile("mbarrier.init.shared::cta.b64 [%0], %1;" ::"r"(b), "r"(c) : "memory"); }
__device__ __forceinline__ void mbar_expect(uint32_t b, int bytes) { asm volatile("mbarrier.arrive.expect_tx.shared::cta.b64 _, [%0], %1;" ::"r"(b), "r"(bytes) : "memory"); }
__device__ __forceinline__ void mbar_arrive(uint32_t b) { asm volatile("mbarrier.arrive.shared::cta.b64 _, [%0];" ::"r"(b) : "memory"); }
__device__ __forceinline__ void mbar_arrive_if(uint32_t b, uint32_t pred) {
  asm volatile("{\n.reg .pred p;\nsetp.ne.u32 p, %1, 0;\n@p mbarrier.arrive.shared::cta.b64 _, [%0];\n}" ::"r"(b), "r"(pred) : "memory");
}
#define WAIT_LIMIT "2000000"
#define DIE_ADDR "l"(0ull)
#define DIE_ST "st.global.u32 [%2], %1;\n"
__device__ __forceinline__ void die() { asm volatile("st.global.u32 [%0], %1;" ::"l"(0ull), "r"(0) : "memory"); }
__device__ __forceinline__ void mbar_wait(uint32_t b, uint32_t ph) {
  asm volatile(
      "{\n.reg .pred p;\n.reg .u32 c;\nmov.u32 c, 0;\n"
      "W:\nmbarrier.try_wait.parity.shared::cta.b64 p, [%0], %1, 1000;\n@p bra D;\n"
      "add.u32 c, c, 1;\nsetp.lt.u32 p, c, " WAIT_LIMIT ";\n@p bra W;\n" DIE_ST
      "D:\n}" ::"r"(b), "r"(ph), DIE_ADDR : "memory");
}
__device__ __forceinline__ uint32_t mbar_test(uint32_t b, uint32_t ph) {
  uint32_t ok;
  asm volatile("{\n.reg .pred p;\nmbarrier.test_wait.parity.shared::cta.b64 p, [%1], %2;\nselp.u32 %0, 1, 0, p;\n}" : "=r"(ok) : "r"(b), "r"(ph) : "memory");
  return ok;
}
__device__ __forceinline__ void cnt_arrive(int idx) {
  asm volatile("red.release.gpu.global.add.u32 [%0], 1;" ::"l"(&g_cnt[idx * CNT_STRIDE]) : "memory");
}
__device__ __forceinline__ void cnt_wait(uint32_t idx, uint32_t target) {
  asm volatile(
      "{\n.reg .pred p;\n.reg .u32 c, v;\nmov.u32 c, 0;\n"
      "W:\nld.acquire.gpu.global.u32 v, [%3];\nsub.u32 v, v, %1;\nsetp.ge.s32 p, v, 0;\n@p bra D;\n"
      "add.u32 c, c, 1;\nsetp.lt.u32 p, c, " WAIT_LIMIT ";\n@p bra W;\n" DIE_ST
      "D:\n}" ::"r"(idx | 0x80000000u), "r"(target), DIE_ADDR, "l"(&g_cnt[idx * CNT_STRIDE]) : "memory");
}
__device__ __forceinline__ void release_x(uint32_t fdone, uint32_t ph, int cnt, int n, uint32_t mask) {
#pragma unroll 1
  for (int k = 0; k < n;) {
    int e = k + __ffs(mask >> k);
    mbar_wait(fdone + 8 * (e - 1), ph);
    asm volatile("fence.release.gpu;" ::: "memory");
    asm volatile("red.relaxed.gpu.global.add.u32 [%0], 1;" ::"l"(&g_cnt[(cnt + e - 1) * CNT_STRIDE]) : "memory");
    k = e;
  }
}
__device__ __forceinline__ uint4 lds128(uint32_t a) {
  uint4 v;
  asm volatile("ld.shared.v4.u32 {%0,%1,%2,%3}, [%4];" : "=r"(v.x), "=r"(v.y), "=r"(v.z), "=r"(v.w) : "r"(a) : "memory");
  return v;
}
__device__ __forceinline__ void stat_publish(ulonglong2* p, float s, float qq, uint32_t ep1) {
  const float mean = s * (1.0f / DM);
  const float rstd = rsqrtf(fmaxf(qq * (1.0f / DM) - mean * mean, 0.f) + 1e-5f);
  const unsigned long long tag = (unsigned long long)ep1 << 32;
  asm volatile("st.relaxed.gpu.global.v2.u64 [%0], {%1, %2};" ::"l"(p), "l"(tag | __float_as_uint(rstd)), "l"(tag | __float_as_uint(-mean)) : "memory");
}
__device__ __forceinline__ void stat_gather(const ulonglong2* p, uint32_t tag, float* rsd, float* md, float* rs2) {
  unsigned long long a[4], b[4];
#pragma unroll 1
  for (uint32_t it = 0;; it++) {
    bool ok = true;
#pragma unroll
    for (int i = 0; i < 4; i++) asm volatile("ld.relaxed.gpu.global.v2.u64 {%0, %1}, [%2];" : "=l"(a[i]), "=l"(b[i]) : "l"(p + i * 32) : "memory");
#pragma unroll
    for (int i = 0; i < 4; i++) ok = ok && (uint32_t)(a[i] >> 32) == tag && (uint32_t)(b[i] >> 32) == tag;
    if (ok) break;
    if (it > 2000000u) { die(); break; }
  }
#pragma unroll
  for (int i = 0; i < 4; i++) {
    rsd[(i & 1) * 64 + (i >> 1) * 2] = __uint_as_float((uint32_t)a[i]);
    if (md) md[(i & 1) * 64 + (i >> 1) * 2] = __uint_as_float((uint32_t)b[i]);
    if (rs2) rs2[i * 8] = __uint_as_float((uint32_t)a[i]);
  }
}
__device__ __forceinline__ void pace(uint32_t t0, uint32_t dt) { while (clock32() - t0 < dt) __nanosleep(20); }
__device__ __forceinline__ void spin_until(uint32_t t) {
  asm volatile("{\n.reg .pred p;\n.reg .u32 c;\nW:\nmov.u32 c, %%clock;\nsub.u32 c, c, %0;\nsetp.lt.s32 p, c, 0;\n@p nanosleep.u32 40;\n@p bra W;\n}" ::"r"(t) : "memory");
}
__device__ __forceinline__ void tma2d(uint32_t dst, const CUtensorMap* m, uint32_t bar, int c0, int c1) {
  asm volatile("cp.async.bulk.tensor.2d.shared::cluster.global.mbarrier::complete_tx::bytes [%0], [%1, {%3, %4}], [%2];" ::"r"(dst), "l"(m), "r"(bar), "r"(c0), "r"(c1) : "memory");
}
__device__ __forceinline__ void tma2d_ef(uint32_t dst, const CUtensorMap* m, uint32_t bar, int c0, int c1) {
  asm volatile("{\n.reg .b64 pol;\ncreatepolicy.fractional.L2::evict_first.b64 pol, 1.0;\n"
               "cp.async.bulk.tensor.2d.shared::cluster.global.mbarrier::complete_tx::bytes.L2::cache_hint [%0], [%1, {%3, %4}], [%2], pol;\n}"
               ::"r"(dst), "l"(m), "r"(bar), "r"(c0), "r"(c1) : "memory");
}
__device__ __forceinline__ void tma3d(uint32_t dst, const CUtensorMap* m, uint32_t bar, int c0, int c1, int c2) {
  asm volatile("cp.async.bulk.tensor.3d.shared::cluster.global.mbarrier::complete_tx::bytes [%0], [%1, {%3, %4, %5}], [%2];" ::"r"(dst), "l"(m), "r"(bar), "r"(c0), "r"(c1), "r"(c2) : "memory");
}
__device__ __forceinline__ void tma3d_mc(uint32_t dst, const CUtensorMap* m, uint32_t bar, int c0, int c1, int c2) {
  asm volatile("cp.async.bulk.tensor.3d.shared::cluster.global.mbarrier::complete_tx::bytes.multicast::cluster [%0], [%1, {%3, %4, %5}], [%2], %6;"
               ::"r"(dst), "l"(m), "r"(bar), "r"(c0), "r"(c1), "r"(c2), "h"((uint16_t)3) : "memory");
}
__device__ __forceinline__ uint32_t map_rank(uint32_t a, uint32_t rank) {
  uint32_t v;
  asm("mapa.shared::cluster.u32 %0, %1, %2;" : "=r"(v) : "r"(a), "r"(rank));
  return v;
}
__device__ __forceinline__ void mbar_arrive_cl_if(uint32_t b, uint32_t pred) {
  asm volatile("{\n.reg .pred p;\nsetp.ne.u32 p, %1, 0;\n@p mbarrier.arrive.shared::cluster.b64 _, [%0];\n}" ::"r"(b), "r"(pred) : "memory");
}
__device__ __forceinline__ void bulk_pf(const void* p, int bytes) {
  asm volatile("cp.async.bulk.prefetch.L2.global [%0], %1;" ::"l"(p), "r"(bytes) : "memory");
}
__device__ __forceinline__ void tma_st2d(const CUtensorMap* m, uint32_t src, int c0, int c1) {
  asm volatile("cp.async.bulk.tensor.2d.global.shared::cta.tile.bulk_group [%0, {%2, %3}], [%1];" ::"l"(m), "r"(src), "r"(c0), "r"(c1) : "memory");
}
__device__ __forceinline__ void tma_red2d(const CUtensorMap* m, uint32_t src, int c0, int c1) {
  asm volatile("cp.reduce.async.bulk.tensor.2d.global.shared::cta.add.tile.bulk_group [%0, {%2, %3}], [%1];" ::"l"(m), "r"(src), "r"(c0), "r"(c1) : "memory");
}
__device__ __forceinline__ void bulk_commit() { asm volatile("cp.async.bulk.commit_group;" ::: "memory"); }
__device__ __forceinline__ void bulk_wait0() { asm volatile("cp.async.bulk.wait_group 0;" ::: "memory"); }
__device__ __forceinline__ void fence_async_smem() { asm volatile("fence.proxy.async.shared::cta;" ::: "memory"); }
__device__ __forceinline__ void fence_async_global() { asm volatile("fence.proxy.async.global;" ::: "memory"); }
__device__ __forceinline__ void wg_fence() { asm volatile("wgmma.fence.sync.aligned;" ::: "memory"); }
__device__ __forceinline__ void wg_commit() { asm volatile("wgmma.commit_group.sync.aligned;" ::: "memory"); }
template <int N> __device__ __forceinline__ void wg_wait() { asm volatile("wgmma.wait_group.sync.aligned %0;" ::"n"(N) : "memory"); }
__device__ __forceinline__ uint32_t pk(float a, float b) {
  uint32_t r;
  asm("cvt.rn.bf16x2.f32 %0, %1, %2;" : "=r"(r) : "f"(b), "f"(a));
  return r;
}
__device__ __forceinline__ uint32_t pk_relu(float a, float b) {
  uint32_t r;
  asm("cvt.rn.relu.bf16x2.f32 %0, %1, %2;" : "=r"(r) : "f"(b), "f"(a));
  return r;
}
__device__ __forceinline__ float bf_lo(uint32_t v) { return __uint_as_float(v << 16); }
__device__ __forceinline__ float bf_hi(uint32_t v) { return __uint_as_float(v & 0xffff0000u); }
__device__ __forceinline__ void stsm4(uint32_t addr, uint32_t a0, uint32_t a1, uint32_t a2, uint32_t a3) {
  asm volatile("stmatrix.sync.aligned.m8n8.x4.shared.b16 [%0], {%1,%2,%3,%4};" ::"r"(addr), "r"(a0), "r"(a1), "r"(a2), "r"(a3));
}
template <int R> __device__ __forceinline__ void reg_fence(float (&d)[R]) {
#pragma unroll
  for (int i = 0; i < R; i++) asm volatile("" : "+f"(d[i])::"memory");
}
constexpr uint32_t DESC_HI_128 = (1024u >> 4) | (1u << 30);
__device__ __forceinline__ uint64_t desc(uint32_t lo, uint32_t hi) {
  uint64_t d;
  asm("mov.b64 %0, {%1, %2};" : "=l"(d) : "r"(lo), "r"(hi));
  return d;
}

__device__ __forceinline__ void sum8(uint4 v, float& s, float& q) {
  float a;
  a = bf_lo(v.x); s += a; q = fmaf(a, a, q);  a = bf_hi(v.x); s += a; q = fmaf(a, a, q);
  a = bf_lo(v.y); s += a; q = fmaf(a, a, q);  a = bf_hi(v.y); s += a; q = fmaf(a, a, q);
  a = bf_lo(v.z); s += a; q = fmaf(a, a, q);  a = bf_hi(v.z); s += a; q = fmaf(a, a, q);
  a = bf_lo(v.w); s += a; q = fmaf(a, a, q);  a = bf_hi(v.w); s += a; q = fmaf(a, a, q);
}

__device__ __forceinline__ int frag_pos(int row) { return (((row >> 4) & 3) * 8 + (row & 7)) * 4 + ((row >> 3) & 1) + (row >> 6) * 2; }
__device__ __forceinline__ float2 lds64f(uint32_t a) {
  float2 v;
  asm volatile("ld.shared.v2.f32 {%0,%1}, [%2];" : "=f"(v.x), "=f"(v.y) : "r"(a) : "memory");
  return v;
}
__device__ __forceinline__ float4 lds128f(uint32_t a) {
  float4 v;
  asm volatile("ld.shared.v4.f32 {%0,%1,%2,%3}, [%4];" : "=f"(v.x), "=f"(v.y), "=f"(v.z), "=f"(v.w) : "r"(a) : "memory");
  return v;
}

__device__ __forceinline__ int doff(int layer, int s) { return (layer && s == 3) ? OFF_A + 6 * A_SLOT : OFF_B + (s & 3) * D_SLOT; }

constexpr int G3A_C1 = 8;
constexpr int G3B_C1 = 6;
constexpr int G3A_C2 = 12;
constexpr int G3B_C2 = 10;
constexpr int CLD_DT = 900;
constexpr int FLUSH_DT = 800;
constexpr int FLUSH_DT_D = 450;
constexpr int CPF2_DT = 400;
constexpr int HPF_D_START = 66000;
constexpr int HW1_START = 10000;
constexpr int XEARLY4 = 6;
constexpr int FLUSH_DT4 = 870;
constexpr int RELMASK2 = 0x1AC;
constexpr int RELMASK4 = 0x12A;
constexpr int FLUSH_DT_A = 800;
constexpr int AG_DT = 200;
constexpr int CL0_T0 = 1000;
constexpr int REST_T0 = 700;
constexpr int CE1 = 5;
constexpr int CE1_DT = 1100;
constexpr int CL0_DT = 1250;
constexpr int CL0_DT2 = 1000;
constexpr int CL0_N = 6;
constexpr int HPF_W2A = 52000;
constexpr int YGAP = 150;
constexpr int X2_DT = 700;
constexpr int X2_DT2 = 300;
constexpr int FLUSH_DT_E = 820;

__global__ void __launch_bounds__(384, 1)
fnet_ffn_kernel(const __grid_constant__ Maps maps, const __nv_bfloat16* __restrict__ xin, const __nv_bfloat16* __restrict__ cre,
                const __nv_bfloat16* __restrict__ cim, const __nv_bfloat16* __restrict__ dre,
                const __nv_bfloat16* __restrict__ dim,
                __nv_bfloat16* xout) {
  extern __shared__ __align__(1024) unsigned char smem[];
  const uint32_t sb = __shfl_sync(0xffffffffu, (uint32_t)__cvta_generic_to_shared(smem), 0);
  constexpr uint32_t sbd = 1024;
  const int tid = threadIdx.x;
  const int wg = __shfl_sync(0xffffffffu, tid >> 7, 0);
  const int warp = __shfl_sync(0xffffffffu, (tid >> 5) & 3, 0);
  const int lane = tid & 31;
  if (blockIdx.x < NHELP) {
    if (tid == 0) atomicAdd(&g_cnt[CNT_TICKET * CNT_STRIDE], 1u);
    const uint32_t th0 = clock32();
    constexpr int HS = 16, HG = DFF / 192 / NHELP;
    const uint32_t hb = sb + HS * B_SLOT + 8192;
    if (tid == 0) {
#pragma unroll
      for (int i = 0; i < 2 * HS; i++) mbar_init(hb + 8 * i, 1);
      asm volatile("fence.mbarrier_init.release.cluster;" ::: "memory");
    }
    for (int i = tid; i < 2048; i += 384) reinterpret_cast<uint32_t*>(smem + HS * B_SLOT)[i] = 0x3f803f80u;
    fence_async_smem();
    __syncthreads();
    if (wg == 0) {
      int slot = 0, ph = 0;
#pragma unroll 1
      for (int g = 0; g < HG; g++) {
        float acc[96];
#pragma unroll
        for (int i = 0; i < 96; i++) acc[i] = 0.f;
#pragma unroll 1
        for (int st = 0; st < 18; st++) {
          mbar_wait(hb + 8 * slot, ph);
          const uint32_t blo = (((sbd + slot * B_SLOT) >> 4) | ((4096u >> 4) << 16));
          const uint64_t da = desc(((sbd + HS * B_SLOT) >> 4) | (1u << 16), DESC_HI_128);
          wg_fence();
          wgmma_n192<1, false>(acc, da, desc(blo, DESC_HI_128));
          wgmma_n192<1, false>(acc, da, desc(blo + 128, DESC_HI_128));
          wg_commit();
          wg_wait<1>();
          mbar_arrive_if(hb + 8 * (HS + ((slot + HS - 1) & (HS - 1))), tid == 0 && (g | st));
          if (++slot == HS) { slot = 0; ph ^= 1; }
        }
        wg_wait<0>();
        reg_fence(acc);
        if (tid < 4) {
#pragma unroll
          for (int b = 0; b < 24; b++)
            *reinterpret_cast<float2*>(g_cs1 + ((blockIdx.x * HG + g) / 3) * 576 + tid * 144 + (g % 3) * 48 + b * 2) = make_float2(acc[b * 4], acc[b * 4 + 1]);
        }
      }
      __syncwarp();
      if (tid == 0) { cnt_arrive(CNT_CS); }
    } else if (tid == 128) {
      int slot = 0, ph = 1;
      pace(th0, HW1_START);
#pragma unroll 1
      for (int i = 0; i < HG * 18; i++) {
        mbar_wait(hb + 8 * (HS + slot), ph);
        mbar_expect(hb + 8 * slot, B_SLOT);
        tma3d(sb + slot * B_SLOT, &maps.w1, hb + 8 * slot, 0, (i % 18) * 32, (blockIdx.x * HG + i / 18) * 3);
        if (++slot == HS) { slot = 0; ph ^= 1; }
      }
      pace(th0, HPF_W2A);
#pragma unroll 1
      for (int i = 0; i < 108; i++)
        asm volatile("cp.async.bulk.prefetch.tensor.3d.L2.global.tile [%0, {%1, %2, %3}];"
                     ::"l"(&maps.w2n), "r"(0), "r"(blockIdx.x * 1152 + (i % 12) * 96), "r"(i / 12) : "memory");
      pace(th0, HPF_D_START);
#pragma unroll 1
      for (int i = 0; i < 81; i++) bulk_pf(reinterpret_cast<const char*>((blockIdx.x & 1) ? dim : dre) + ((blockIdx.x >> 1) * 81 + i) * 4096, 4096);
    }
    return;
  }
  const int cta = blockIdx.x - NHELP;
  const int r = cta & 15, p = cta >> 4;
  const int m = p >> 2, q = p & 3;
  const int rank = cta & 1;
  const uint32_t bar0 = sb + OFF_BAR;
#define BAR(i) (bar0 + 8u * (uint32_t)(i))
#define START_SYNC() do { __syncwarp(); asm volatile("barrier.cluster.wait.acquire.aligned;" ::: "memory"); } while (0)

  uint32_t ticket = 0;
  if (elect_one()) {
    const int w12 = wg * 4 + warp;
#pragma unroll
    for (int i = 0; i < 17; i++) mbar_init(BAR(w12 * 17 + i), w12 < 2 ? 4 : (w12 == 2 ? 2 : 1));
    asm volatile("fence.mbarrier_init.release.cluster;" ::: "memory");
    if (w12 == 8) {
      fence_async_smem();
      mbar_expect(BAR(BAR_XF), A_SLOT);
      tma2d(sb + OFF_A, &maps.xin, BAR(BAR_XF), 0, r * 128);
    }
  }
  __syncwarp();
  asm volatile("barrier.cluster.arrive.relaxed.aligned;" ::: "memory");
  if (wg == 2 && warp == 0) {
    START_SYNC();
    if (elect_one()) {
#pragma unroll 1
      for (int k = 0; k < 4; k++) {
        mbar_expect(BAR(BAR_DF + k), D_SLOT);
        if ((k & 1) == rank) tma3d_mc(sb + OFF_B + k * D_SLOT, m ? &maps.di : &maps.dr, BAR(BAR_DF + k), k * 64, q * 48, 0);
        mbar_expect(BAR(BAR_XF + k + 1), A_SLOT);
        tma2d(sb + OFF_A + (k + 1) * A_SLOT, &maps.xin, BAR(BAR_XF + k + 1), (k + 1) * 64, r * 128);
      }
    }
    __syncwarp();
  }
  if (tid == 320) asm volatile("atom.relaxed.gpu.global.add.u32 %0, [%1], 1;" : "=r"(ticket) : "l"(&g_cnt[CNT_TICKET * CNT_STRIDE]));

  if (wg == 2) {
    asm volatile("setmaxnreg.dec.sync.aligned.u32 40;");
    if (warp & 1) START_SYNC();
    if (warp == 0) {
      const CUtensorMap* mD = m ? &maps.di : &maps.dr;
      if (elect_one()) {
        int slot = 0, ph = 1;
#pragma unroll 1
        for (int layer = 0; layer < 2; layer++) {
#pragma unroll 1
          for (int s = 0; s < 9; s++) {
            if (s < 3) {
              const int nacq = (layer && s == 1) ? 1 : 2;
#pragma unroll 1
              for (int i = 0; i < nacq; i++) {
                mbar_wait(BAR(BAR_BEMPTY + slot), ph);
                mbar_arrive(BAR(BAR_BFULL + slot));
                if (++slot == NB + 1 - layer) { slot = 0; ph ^= 1; }
              }
            } else if (layer && s == 7) {
              mbar_wait(BAR(BAR_SENTY), 0);
              mbar_arrive_cl_if(map_rank(BAR(BAR_STGF), 0), 1);
              mbar_arrive_cl_if(map_rank(BAR(BAR_STGF), 1), 1);
              mbar_wait(BAR(BAR_STGF), 0);
            } else if (s > 3) {
              mbar_wait(BAR(BAR_DREL + s - 4), layer);
            }
            if (layer || s >= 4) {
              mbar_expect(BAR(BAR_DF + s), D_SLOT);
              if ((s & 1) == rank) tma3d_mc(sb + doff(layer, s), mD, BAR(BAR_DF + s), s * 64, q * 48, 0);
              const int k = s + 1;
              if (layer == 0 && k < 9) {
                mbar_expect(BAR(BAR_XF + k), A_SLOT);
                tma2d(sb + OFF_A + k * A_SLOT, &maps.xin, BAR(BAR_XF + k), k * 64, r * 128);
              }
            }
          }
#pragma unroll 1
          for (int sg = -8; sg < 18; sg++) {
            const CUtensorMap* mm;
            int row, atom, n, dk = 32, dk2 = 0;
            if (sg < 4) {
              mm = &maps.abld; row = (layer * 2 + m) * SEQ + q * 512;
              if (sg < 0) {
                mbar_wait(BAR(BAR_ABOK + 8 + sg), layer);
                row += (sg & 3) * 128 + (sg & 4) * 16; atom = 0; n = 2;
              } else {
                if (!(sg & 1)) mbar_wait(BAR(sg ? BAR_FOK : BAR_AB1), layer);
                row += (sg & 1) * 64; atom = (sg >> 1) * 3 + 3; n = 8; dk2 = 64;
              }
            } else if (sg < 13) {
              mm = &maps.w1;
              if (sg < 10) {
                const int cw = sg & 1;
                const int c1 = cw ? G3B_C1 : G3A_C1, c2 = cw ? G3B_C2 : G3A_C2;
                const int lo = sg < 6 ? 0 : (sg < 8 ? c1 : c2), hi = sg < 6 ? c1 : (sg < 8 ? c2 : 18);
                atom = p * 9 + cw * 3; row = lo * 32; n = hi - lo;
              } else { atom = p * 9 + 6; row = (12 - sg) * 192; n = 6; }
            } else {
              row = p * 576;
              atom = (sg - 13) * 2;
              if (sg < 17) { mm = &maps.w2; n = 12; dk = 48; }
              else { mm = &maps.w2n; n = 6; dk = 96; }
            }
            const uint32_t fb0 = BAR(BAR_BFULL);
            const int nsl = sg < 13 ? NB + 1 : NB;
            if (sg == 13) {
              mbar_wait(BAR(BAR_BEMPTY), ph);
              mbar_arrive(BAR(BAR_BFULL));
              mbar_arrive_cl_if(map_rank(BAR(BAR_BEMPTY), 0), 1);
              mbar_arrive_cl_if(map_rank(BAR(BAR_BEMPTY), 1), 1);
              slot = 1;
            }
            if (sg == 17) asm volatile("prefetch.tensormap [%0];" ::"l"(mD) : "memory");
            if (sg == -6) mbar_wait(BAR(BAR_STG2), layer);
#pragma unroll 1
            for (int i = 0; i < n; i++) {
              mbar_wait(BAR(BAR_BEMPTY + slot), ph);
              mbar_expect(fb0 + 8 * slot, B_SLOT);
              if ((i & 1) == rank) tma3d_mc(sb + OFF_B + slot * B_SLOT, mm, fb0 + 8 * slot, 0, row, atom);
              row += dk + (i & 1) * dk2;
              if (++slot == nsl) { slot = 0; ph ^= 1; }
            }
          }
        }
#pragma unroll 1
        for (int i = 0; i < NB; i++) {
          mbar_wait(BAR(BAR_BEMPTY + slot), ph);
          if (++slot == NB) { slot = 0; ph ^= 1; }
        }
      }
    } else if (warp == 1) {
      if (lane == 0) {
        asm volatile("prefetch.tensormap [%0];" ::"l"(m ? &maps.ci : &maps.cr) : "memory");
        asm volatile("prefetch.tensormap [%0];" ::"l"(&maps.abst) : "memory");
        asm volatile("prefetch.tensormap [%0];" ::"l"(&maps.abld) : "memory");
      }
      mbar_wait(BAR(BAR_EPOCH), 0);
      const uint32_t ep1 = *reinterpret_cast<volatile uint32_t*>(smem + OFF_EPOCH);
      {
        unsigned long long a[3], b[3];
#pragma unroll 1
        for (uint32_t it = 0;; it++) {
          bool ok = true;
#pragma unroll
          for (int i = 0; i < 3; i++)
            asm volatile("ld.relaxed.gpu.global.v2.u64 {%0, %1}, [%2];" : "=l"(a[i]), "=l"(b[i]) : "l"(&g_csd[p * 144 + min(lane + i * 32, 71) * 2]) : "memory");
#pragma unroll
          for (int i = 0; i < 3; i++) ok = ok && (uint32_t)(a[i] >> 32) == ep1 && (uint32_t)(b[i] >> 32) == ep1;
          if (ok) break;
          if (it > 2000000u) { die(); break; }
        }
#pragma unroll
        for (int i = 0; i < 3; i++)
          reinterpret_cast<float2*>(smem + OFF_CSD)[(min(lane + i * 32, 71) & 3) * 18 + (min(lane + i * 32, 71) >> 2)] = make_float2(__uint_as_float((uint32_t)a[i]), __uint_as_float((uint32_t)b[i]));
        __syncwarp();
        mbar_arrive_if(BAR(BAR_CSD), lane == 0);
      }
      if (lane == 0) {
#pragma unroll 1
        for (int layer = 0; layer < 2; layer++) {
          const int abrow = (layer * 2 + m) * SEQ + r * 128;
          const int abcnt = CNT_AB + ((layer * 2 + m) * 16 + r) * 4 + 1;
          mbar_wait(BAR(BAR_ABH), layer);
          cnt_arrive(abcnt - 1);
          mbar_wait(BAR(BAR_ABH + 1), layer);
          cnt_arrive(abcnt);
          mbar_wait(BAR(BAR_ABSTG), layer);
          mbar_wait(BAR(BAR_ABOK), layer);
          spin_until(clock32() + REST_T0);
          tma_st2d(&maps.abst, sb + OFF_A + 7 * A_SLOT, 192 + q * 48, abrow);
          bulk_commit();
          bulk_wait0();
          mbar_arrive(BAR(BAR_A7));
          cnt_arrive(abcnt + 1);
          tma_st2d(&maps.abst, sb + OFF_A + 8 * A_SLOT, 384 + q * 48, abrow);
          bulk_commit();
          bulk_wait0();
          mbar_arrive(BAR(BAR_A8));
          cnt_arrive(abcnt + 2);
          release_x(BAR(BAR_FDONE), layer, CNT_X + (layer * 2 * 16 + r) * 9, 6, RELMASK2);
          {
            uint32_t tn = 0;
#pragma unroll 1
            for (int i = 0; i < 8; i++) {
              if ((i & 3) == 0) mbar_wait(BAR(BAR_FDONE + 7 + (i >> 2)), layer);
              if (i == 0) tn = clock32();
              spin_until(tn);
              tma_red2d(&maps.xred, sb + OFF_A + 7 * A_SLOT + i * 4096, 448 + (i >> 2) * 64, r * 128 + (i & 3) * 32);
              tma_red2d(&maps.xred, sb + OFF_A + 7 * A_SLOT + i * 4096 + 2048, 448 + (i >> 2) * 64, r * 128 + (i & 3) * 32 + 16);
              tn += AG_DT;
              if (i == 3) {
                bulk_commit();
                mbar_wait(BAR(BAR_FDONE + 6), layer);
                bulk_wait0();
                mbar_arrive(BAR(BAR_SENT));
              }
            }
            bulk_commit();
            bulk_wait0();
            cnt_arrive(CNT_X + (layer * 2 * 16 + r) * 9 + 8);
          }
          mbar_wait(BAR(BAR_XRD), layer);
#pragma unroll 1
          for (int s = 0; s < 3; s++) {
            mbar_wait(BAR(BAR_RG3C + s), layer);
            mbar_wait(BAR(BAR_RG3B + 6 + s), layer);
            mbar_expect(BAR(BAR_X1F + 9 + s), A_SLOT);
            tma2d(sb + OFF_A + (6 + s) * A_SLOT, &maps.xld, BAR(BAR_X1F + 9 + s), s * 64, r * 128);
          }
#pragma unroll 1
          for (int s = 0; s < 3; s++) mbar_wait(BAR(BAR_X1F + 9 + s), layer);
          cnt_arrive(CNT_G3 + layer * 16 + r);
          cnt_wait(CNT_G3 + layer * 16 + r, ep1 * 8);
          mbar_arrive(BAR(BAR_FOK + 1));
          if (layer == 0) release_x(BAR(BAR_FDONE + 9), 0, CNT_X + (16 + r) * 9, 6, RELMASK4);
          asm volatile("prefetch.tensormap [%0];" ::"l"(&maps.xh) : "memory");
          mbar_wait(BAR(BAR_FDONE + 17), layer);
          tma_red2d(&maps.xh, sb + OFF_A + 8 * A_SLOT, 512, r * 128);
          if (layer == 0) {
            bulk_commit();
            mbar_wait(BAR(BAR_FDONE + 15), 0);
            bulk_wait0();
            mbar_arrive(BAR(BAR_SENTX));
            mbar_wait(BAR(BAR_FDONE + 16), 0);
            spin_until(clock32() + YGAP);
#pragma unroll 1
            for (int i = 0; i < 8; i++) tma_red2d(&maps.xred, sb + OFF_STG + i * 2048, 384 + (i & 1) * 64, r * 128 + 64 + (i >> 1) * 16);
            bulk_commit();
          }
          tma_red2d(&maps.xh, sb + OFF_A + 8 * A_SLOT + 8192, 512, r * 128 + 64);
          bulk_commit();
          if (layer == 0) {
            asm volatile("cp.async.bulk.wait_group 1;" ::: "memory");
            mbar_arrive(BAR(BAR_SENTY));
          }
          bulk_wait0();
          if (layer == 0) {
            cnt_arrive(CNT_X + (16 + r) * 9 + 8);
          }
        }
      }
    } else if (warp == 2) {
      START_SYNC();
      if ((sb & 0x3FFFFu) != sbd) die();
      const uint32_t ep1 = __shfl_sync(0xffffffffu, ticket, 0) / NGRID + 1;
      if (lane == 0) {
        *reinterpret_cast<volatile uint32_t*>(smem + OFF_EPOCH) = ep1;
        mbar_arrive(BAR(BAR_EPOCH));
      }
      {
        stat_gather(&g_stat[r * 128 + lane], ep1, reinterpret_cast<float*>(smem + OFF_RS) + frag_pos(lane), reinterpret_cast<float*>(smem + OFF_MEAN) + frag_pos(lane), nullptr);
        __syncwarp();
        mbar_arrive_if(BAR(BAR_STAT), lane == 0);
        mbar_arrive_if(BAR(BAR_STATY), lane == 0);
      }
#pragma unroll 1
      for (int ph4 = 0; ph4 < 4; ph4++) {
        const int layer = ph4 >> 1, second = ph4 & 1;
        if (ph4) {
          const bool low = !second && lane >= 9;
          const int pl = (ph4 - 1) >> 1, k = min(low ? lane - 3 : lane, 8);
          const uint32_t fd = BAR(BAR_FDONE + (second ? 0 : 9));
          const uint32_t fr = BAR(second ? (k < 8 ? BAR_RG2 + k : BAR_RG1 + 8) : (k < 8 ? BAR_RG1 + 3 : BAR_RG4 + 8));
          const uint32_t fp = second ? pl : k < 8;
          const uint32_t fb = BAR(low ? BAR_XFY - 6 + k : (second ? BAR_X1F : BAR_XF) + k);
          const int kr = k - 1 + __ffs((second ? RELMASK2 : RELMASK4) >> k);
          const uint32_t* flag = &g_cnt[(CNT_X + ((ph4 - 1) * 16 + r) * 9 + kr - (!second && !low && k >= 6)) * CNT_STRIDE];
          uint32_t state = lane >= (second ? 9 : 12) ? 2 : 0;
          bool needm = second;
          uint32_t tgo = 0;
          if (second) { mbar_wait(BAR(BAR_STAT), layer); mbar_wait(BAR(BAR_STATY), layer); }
          mbar_wait(fd, pl);
#pragma unroll 1
          for (uint32_t it = 0;; it++) {
            bool polled = false;
            if (state == 0 && mbar_test(fd + 8 * kr, pl)) {
              uint32_t c;
              asm volatile("ld.acquire.gpu.global.u32 %0, [%1];" : "=r"(c) : "l"(flag) : "memory");
              polled = true;
              if ((int32_t)(c - ep1 * 8) >= 0) {
                fence_async_global();
                state = 1;
                tgo = clock32() + (second ? (k < 3 ? k * X2_DT : (kr - k < 2 && k < 8 && k > 3 ? (1 - (kr - k)) * X2_DT2 : 0)) : 0);
                if (!second && k < XEARLY4) { mbar_arrive(BAR(BAR_XOK + k)); state = 2; }
              }
            }
            if (state == 1 && (int32_t)(clock32() - tgo) >= 0 && mbar_test(fr, fp)) {
              mbar_expect(fb, second ? A_SLOT : A_SLOT / 2);
              tma2d(sb + OFF_A + k * A_SLOT + low * 8192, second ? &maps.xld : &maps.xh, fb, k * 64, r * 128 + low * 64);
              state = 2;
            }
            if (needm && (__ballot_sync(0xffffffffu, state != 0) & 0xff) == 0xff) {
              __syncwarp();
              float4 t;
              asm volatile("ld.relaxed.gpu.global.v4.f32 {%0,%1,%2,%3}, [%4];" : "=f"(t.x), "=f"(t.y), "=f"(t.z), "=f"(t.w) : "l"(&g_rsum[layer * SEQ + r * 128 + lane * 4]) : "memory");
              float4* mp = reinterpret_cast<float4*>(smem + OFF_MEAN) + lane;
              const float4 o = *mp;
              constexpr float inv = -1.0f / DM;
              *mp = make_float4(fmaf(t.x, inv, o.x), fmaf(t.y, inv, o.y), fmaf(t.z, inv, o.z), fmaf(t.w, inv, o.w));
              __syncwarp();
              mbar_arrive_if(BAR(BAR_STAT + 1), lane == 0);
              needm = false;
            }
            if (__all_sync(0xffffffffu, state == 2)) break;
            if (!__any_sync(0xffffffffu, polled)) __nanosleep(100);
            if (it > 4000000u) { die(); break; }
          }
        }
        if (!second) {
          int idx = CNT_AB + ((layer * 2 + m) * 16 + q * 4 + (lane & 3)) * 4 + (lane >> 2);
          uint32_t target = ep1 * 4;
          if (lane == 16 || lane == 17) idx = CNT_AB + ((layer * 2 + lane - 16) * 16 + r) * 4 + 1;
          if (lane == 18) { idx = CNT_XINIT + r; target = ep1 * 32; }
          uint32_t pend = lane < 19, pm = 0x7ffff;
          mbar_wait(BAR(BAR_RG1 + 4), layer);
#pragma unroll 1
          for (uint32_t it = 0; pm; it++) {
            if (pend && (lane < 4 || !(pm & 15))) {
              uint32_t v;
              asm volatile("ld.acquire.gpu.global.u32 %0, [%1];" : "=r"(v) : "l"(&g_cnt[idx * CNT_STRIDE]) : "memory");
              if ((int32_t)(v - target) >= 0) {
                fence_async_global();
                if (lane < 8) mbar_arrive(BAR(BAR_ABOK + lane));
                pend = 0;
              }
            }
            __syncwarp();
            const uint32_t nm = __ballot_sync(0xffffffffu, pend);
            mbar_arrive_if(BAR(BAR_AB1), lane == 0 && (pm & 0xf00) && !(nm & 0xf00));
            pm = nm;
            if (it > 2000000u) { die(); break; }
          }
          __syncwarp();
          mbar_arrive_if(BAR(BAR_FOK), lane == 0);
        }
      }
    } else {
      const CUtensorMap* mC = m ? &maps.ci : &maps.cr;
      const char* cbase = reinterpret_cast<const char*>((m ? cim : cre) + (size_t)(r * 128 + (lane >> 1)) * SEQ + q * 512) + (lane & 1) * 128;
      asm volatile("prefetch.global.L2 [%0];" ::"l"(cbase));
      const int myrow = r * 128 + p * 16 + (lane >> 1);
      auto cload = [&](int k) {
        if (elect_one()) {
          mbar_expect(BAR(BAR_CF + k), A_SLOT);
          tma2d_ef(sb + OFF_A + k * A_SLOT, mC, BAR(BAR_CF + k), q * 512 + (k & 3) * 128 + (k >> 2) * 64, r * 128);
        }
        __syncwarp();
      };
      uint32_t t0 = clock32() + CL0_T0 + (cta & 3) * (CL0_DT / 4);
#pragma unroll 1
      for (int kc = 0; kc < 8; kc++) {
        if (kc == CL0_N) { mbar_wait(BAR(BAR_ABOK), 0); t0 = clock32() + (cta & 3) * (CL0_DT2 / 4); }
        spin_until(t0);
        t0 += kc < CL0_N ? CL0_DT : CL0_DT2;
        mbar_wait(BAR(kc < 7 ? BAR_RG1 + kc : BAR_A7), 0);
        cload(kc);
      }
      mbar_wait(BAR(BAR_EPOCH), 0);
      const uint32_t ep1 = *reinterpret_cast<volatile uint32_t*>(smem + OFF_EPOCH);
#pragma unroll 1
      for (int layer = 0; layer < 2; layer++) {
        if (layer) {
          if (elect_one()) {
#pragma unroll 1
            for (int kt = 0; kt < XEARLY4; kt++) {
              mbar_wait(BAR(BAR_XOK + kt), 0);
              mbar_wait(BAR(BAR_RG4 + kt), 0);
              mbar_expect(BAR(BAR_XF + kt), A_SLOT);
              tma2d(sb + OFF_A + kt * A_SLOT, &maps.xld, BAR(BAR_XF + kt), kt * 64, r * 128);
            }
            mbar_wait(BAR(BAR_SENTX), 0);
            cnt_arrive(CNT_X + (16 + r) * 9 + 7);
          }
          __syncwarp();
          t0 = clock32() + (cta & 3) * (CE1_DT / 4);
#pragma unroll 1
          for (int kc = 0; kc < 8; kc++) {
            if (kc == CE1) { mbar_wait(BAR(BAR_STATY), 1); mbar_wait(BAR(BAR_ABOK), 1); }
            spin_until(t0);
            mbar_wait(BAR(kc < 7 ? BAR_RG1 + kc : BAR_A7), 1);
            if (kc < CE1) mbar_wait(BAR(BAR_RD + kc / 3), 0);
            cload(kc);
            t0 = clock32() + (mbar_test(BAR(BAR_ABOK), 1) ? CLD_DT : CE1_DT);
          }
        }
        float s0 = 0.f, q0 = 0.f, s1 = 0.f, q1 = 0.f;
        const int lr = p * 16 + (lane >> 1);
        const uint32_t src = sb + OFF_A + lr * 128 + ((((lane & 1) * 4) ^ (lr & 7)) << 4);
#pragma unroll 1
        for (int k = 0; k < 9; k++) {
          if (k == 3) {
            mbar_wait(BAR(BAR_SENT), layer);
            if (lane == 0) { cnt_arrive(CNT_X + (layer * 2 * 16 + r) * 9 + 7); }
            __syncwarp();
          }
          if (k == 3) {
            if (layer == 0) cnt_wait(CNT_CS, ep1 * NHELP);
            float4 cs[5];
#pragma unroll
            for (int i = 0; i < 5; i++) cs[i] = __ldcg(reinterpret_cast<const float4*>(g_cs1 + p * 576) + min(lane + i * 32, 143));
#pragma unroll
            for (int i = 0; i < 5; i++) reinterpret_cast<float4*>(smem + OFF_CS1)[min(lane + i * 32, 143) + min(lane + i * 32, 143) / 36] = cs[i];
            __syncwarp();
            mbar_arrive_if(BAR(BAR_CSOK), lane == 0);
          }
          mbar_wait(BAR(BAR_X1F + k), layer);
          uint4 v[4];
#pragma unroll
          for (int i = 0; i < 4; i++) v[i] = lds128((src ^ (i << 4)) + k * A_SLOT);
          sum8(v[0], s0, q0); sum8(v[1], s1, q1); sum8(v[2], s0, q0); sum8(v[3], s1, q1);
        }
        s0 += s1; q0 += q1;
        s0 += __shfl_xor_sync(0xffffffffu, s0, 1);
        q0 += __shfl_xor_sync(0xffffffffu, q0, 1);
        mbar_arrive_if(BAR(BAR_XRD), lane == 0);
        if (!(lane & 1)) stat_publish(&g_stat[(layer + 1) * SEQ + myrow], s0, q0, ep1);
        __syncwarp();
        stat_gather(&g_stat[(layer + 1) * SEQ + r * 128 + lane], ep1, reinterpret_cast<float*>(smem + OFF_RS) + frag_pos(lane), nullptr,
                    reinterpret_cast<float*>(smem + OFF_RS2) + ((lane >> 1) & 3) * 36 + (lane >> 3) * 2 + (lane & 1));
        __syncwarp();
        mbar_arrive_if(BAR(BAR_RSOK), lane == 0);
        if (layer == 0) {
          t0 = clock32();
#pragma unroll 1
          for (int i = 0; i < 32; i++) {
            pace(t0, i * CPF2_DT);
            asm volatile("prefetch.global.L2::evict_normal [%0];" ::"l"(cbase + (size_t)(i & 7) * 16 * SEQ * 2 + (i >> 3) * 256));
          }
        }
      }
    }
  } else {
    asm volatile("setmaxnreg.inc.sync.aligned.u32 232;");
    const uint32_t elect = (tid & 127) == 0;
    const uint32_t lane0 = lane == 0;
    if (wg == 1) {
      const int t = tid & 127;
      const int myrow = r * 128 + p * 16 + (t >> 3);
      const uint4* src = reinterpret_cast<const uint4*>(xin + (size_t)myrow * DM) + (t & 7);
      uint4* dst = reinterpret_cast<uint4*>(xout + (size_t)myrow * DM) + (t & 7);
      const int n = r * 9 + min(t >> 3, 8);
      const uint4* dsrc = reinterpret_cast<const uint4*>((m ? dim : dre) + (size_t)((n / 48) * 192 + q * 48 + n % 48) * DM) + (t & 7);
      float s = 0.f, qq = 0.f, sd = 0.f, s2 = 0.f, q2 = 0.f;
      uint4 v[3], d[3], vn[6], dn[6];
#pragma unroll
      for (int i = 0; i < 3; i++) { v[i] = __ldg(src + i * 8); d[i] = __ldg(dsrc + i * 8); }
#pragma unroll
      for (int i = 0; i < 6; i++) { vn[i] = __ldg(src + 24 + i * 8); dn[i] = __ldg(dsrc + 24 + i * 8); }
      START_SYNC();
#pragma unroll 1
      for (int it = 0; it < 72; it += 24) {
        sum8(v[0], s, qq); sum8(v[1], s2, q2); sum8(v[2], s, qq);
#pragma unroll
        for (int i = 0; i < 3; i++) {
          sd += ((bf_lo(d[i].x) + bf_hi(d[i].x)) + (bf_lo(d[i].y) + bf_hi(d[i].y))) + ((bf_lo(d[i].z) + bf_hi(d[i].z)) + (bf_lo(d[i].w) + bf_hi(d[i].w)));
          dst[it + i * 8] = v[i];
          v[i] = vn[i]; d[i] = dn[i]; vn[i] = vn[i + 3]; dn[i] = dn[i + 3];
        }
      }
      s += s2; qq += q2;
#pragma unroll
      for (int o = 1; o < 8; o <<= 1) {
        s += __shfl_xor_sync(0xffffffffu, s, o);
        qq += __shfl_xor_sync(0xffffffffu, qq, o);
        sd += __shfl_xor_sync(0xffffffffu, sd, o);
      }
      mbar_wait(BAR(BAR_EPOCH), 0);
      const uint32_t ep1 = *reinterpret_cast<volatile uint32_t*>(smem + OFF_EPOCH);
      if ((t & 7) == 0) {
        stat_publish(&g_stat[myrow], s, qq, ep1);
        if (t < 72) asm volatile("st.relaxed.gpu.global.u64 [%0], %1;" ::"l"(&g_csd[p * 144 + n]), "l"(((unsigned long long)ep1 << 32) | __float_as_uint(sd)) : "memory");
      }
      if (t < 32) g_rsum[(t >> 4) * SEQ + r * 128 + p * 16 + (t & 15)] = 0.f;
      __syncwarp();
      if (lane == 0) cnt_arrive(CNT_XINIT + r);
      asm volatile("bar.sync 2, 128;" ::: "memory");
    }

    const int srow = (lane & 7) + ((lane >> 3) & 1) * 8;
    const int schunk = lane >> 4;
    const int frow = warp * 16 + (lane >> 2);
    const uint32_t fpos = (warp * 8 + (lane >> 2)) * 16;
    const uint32_t bfull = BAR(BAR_BFULL);
    const uint32_t bempty = map_rank(BAR(BAR_BEMPTY), lane & 1);
    const uint32_t elect2 = (tid & 127) < 2;
    constexpr uint32_t alo0 = ((sbd + OFF_A) >> 4) | (1u << 16);

#pragma unroll 1
    for (int it = -wg; it < 2; it++) {
      const int layer = max(it, 0);
      const uint32_t live = it >= 0;
      float4 rsf = make_float4(0.f, 0.f, 0.f, 0.f);
      auto rowsums = [&](float (&rsum)[4]) {
#pragma unroll
        for (int i = 0; i < 4; i++) {
          rsum[i] += __shfl_xor_sync(0xffffffffu, rsum[i], 1);
          rsum[i] += __shfl_xor_sync(0xffffffffu, rsum[i], 2);
        }
        const int i = lane & 3;
        const float v = i == 0 ? rsum[0] : (i == 1 ? rsum[1] : (i == 2 ? rsum[2] : rsum[3]));
        asm volatile("red.global.add.f32 [%0], %1;" ::"l"(&g_rsum[layer * SEQ + r * 128 + warp * 32 + lane]), "f"(v) : "memory");
      };
      auto flush = [&](auto& acc0, auto& acc1, auto na, int pi, int atom0) {
        constexpr int NA = decltype(na)::value;
        const int ffn = pi >= 7;
        const uint32_t fdone = BAR(BAR_FDONE + ffn * 9 + atom0);
        mbar_wait(BAR(BAR_FOK + ffn), layer);
        if (atom0) mbar_wait(fdone - 8, layer);
        else if (NA == 3) mbar_wait(BAR(BAR_A8), layer);
        const uint32_t stg = sb + (NA == 3 ? OFF_A + 8 * A_SLOT : OFF_STG) + warp * 4096;
        const uint32_t sad = stg + srow * 128;
        const uint32_t dt = NA == 3 ? (pi == 1 ? FLUSH_DT_A : FLUSH_DT) : (pi == 10 ? FLUSH_DT_D : (pi == 9 ? FLUSH_DT_E : FLUSH_DT4));
        float rs[4];
        if (NA == 3) {
#pragma unroll
          for (int i = 0; i < 4; i++) rs[i] = 0.f;
        } else {
          rs[0] = rsf.x; rs[1] = rsf.y; rs[2] = rsf.z; rs[3] = rsf.w;
        }
        uint32_t tn = clock32() + warp * (dt / 4);
#pragma unroll
        for (int n = 0; n < 2 * NA; n++) {
          const int at = NA == 3 ? n >> 1 : n & 1, hf = NA == 3 ? n & 1 : n >> 1;
          uint32_t w[16];
#pragma unroll
          for (int j = 0; j < 16; j++) {
            const int o = at * 32 + j * 2;
            if (NA == 3) {
              w[j] = (n & 1) ? pk(acc1[o], acc1[o + 1]) : pk(acc0[o], acc0[o + 1]);
              rs[(n & 1) * 2 + (j & 1)] += (n & 1) ? acc1[o] + acc1[o + 1] : acc0[o] + acc0[o + 1];
            } else {
              const float f = rs[hf * 2 + (j & 1)];
              w[j] = hf ? pk(acc1[o] * f, acc1[o + 1] * f) : pk(acc0[o] * f, acc0[o + 1] * f);
            }
          }
#pragma unroll
          for (int j = 0; j < 4; j++)
            stsm4(sad + (n & 1) * 2048 + (((j * 2 + schunk) ^ (srow & 7)) << 4), w[j * 4], w[j * 4 + 1], w[j * 4 + 2], w[j * 4 + 3]);
          if (NA == 3 && n == 5) rowsums(rs);
          fence_async_smem();
          if (n) tn += dt;
          spin_until(tn);
          __syncwarp();
          if (elect_one()) {
            if (!(NA == 2 && n >= 2 && pi == 10 && layer == 0))
              tma_red2d(&maps.xred, stg + (n & 1) * 2048, (atom0 + at) * 64, r * 128 + hf * 64 + warp * 16);
            bulk_commit();
            if (n == 2 * NA - 1) {
              bulk_wait0();
              mbar_arrive(fdone + 8 * (NA - 1));
            } else if (n) {
              asm volatile("cp.async.bulk.wait_group 1;" ::: "memory");
              if (!(n & 1)) mbar_arrive(fdone + 8 * ((n >> 1) - 1));
            }
          }
          __syncwarp();
        }
      };
      if (wg == 0) {
        float acc0[72], acc1[72];
        if (layer == 0) { START_SYNC(); }
        constexpr uint32_t blo0 = (sbd >> 4) | (1u << 16);
        uint32_t ready = 0;
        auto step = [&](int s, auto first) {
          constexpr bool F = decltype(first)::value;
          if (!ready) {
            mbar_wait(BAR(BAR_XF + s), layer);
            mbar_wait(BAR(BAR_DF + s), layer);
            if (F && layer) mbar_wait(BAR(BAR_GO + 15), 0);
          }
          const uint32_t alo = alo0 + s * (A_SLOT >> 4);
          const uint32_t blo = blo0 + (doff(layer, s) >> 4);
          wg_fence();
#pragma unroll
          for (int k = 0; k < 4; k++) {
            if (F && k == 0) {
              wgmma_n144<0, true>(acc0, desc(alo, DESC_HI_128), desc(blo, DESC_HI_128));
              wgmma_n144<0, true>(acc1, desc(alo + 512, DESC_HI_128), desc(blo, DESC_HI_128));
            } else {
              wgmma_n144<0, false>(acc0, desc(alo + k * 2, DESC_HI_128), desc(blo + k * 2, DESC_HI_128));
              wgmma_n144<0, false>(acc1, desc(alo + 512 + k * 2, DESC_HI_128), desc(blo + k * 2, DESC_HI_128));
            }
          }
          wg_commit();
          ready = mbar_test(BAR(BAR_XF + s + 1), layer) & mbar_test(BAR(BAR_DF + min(s + 1, 8)), layer);
          if (!F) {
            wg_wait<1>();
            mbar_arrive_cl_if(bempty + 8 * (BAR_DREL - BAR_BEMPTY - 1 + s), elect2);
            mbar_arrive_if(BAR(BAR_RG1 - 1 + s), elect);
          }
        };
        step(0, TrueT{});
#pragma unroll 1
        for (int s = 1; s < 6; s++) step(s, FalseT{});
        mbar_wait(BAR(BAR_CSD), 0);
        float2 cd[18];
#pragma unroll
        for (int i = 0; i < 9; i++) {
          const float4 t = lds128f(sb + OFF_CSD + (lane & 3) * 144 + i * 16);
          cd[i * 2] = make_float2(t.x, t.y); cd[i * 2 + 1] = make_float2(t.z, t.w);
        }
        const float sg = m ? -1.f : 1.f;
        float2 st[4];
        auto val = [&](const float (&acc)[72], int b, int h, const float2& sv) {
          return pk(fmaf(cd[b].x, sv.y, acc[b * 4 + h * 2]) * sv.x, fmaf(cd[b].y, sv.y, acc[b * 4 + h * 2 + 1]) * sv.x);
        };
        auto tail = [&](float (&acc)[72], auto half) {
          constexpr int H = decltype(half)::value;
#pragma unroll 1
          for (int s = 6; s < 9; s++) {
            if (H == 0) { mbar_wait(BAR(BAR_DF + s), layer); mbar_wait(BAR(BAR_XF + s), layer); }
            else if (layer) mbar_wait(BAR(BAR_XFY - 6 + s), 0);
            const uint32_t alo = alo0 + s * (A_SLOT >> 4) + H * 512;
            const uint32_t blo = blo0 + (doff(layer, s) >> 4);
            wg_fence();
#pragma unroll
            for (int k = 0; k < 4; k++) wgmma_n144<0, false>(acc, desc(alo + k * 2, DESC_HI_128), desc(blo + k * 2, DESC_HI_128));
            wg_commit();
          }
          mbar_wait(BAR(H ? BAR_STATY : BAR_STAT), layer);
          const float2 a = lds64f(sb + OFF_RS + fpos + H * 8), b = lds64f(sb + OFF_MEAN + fpos + H * 8);
          st[H * 2] = make_float2(a.x * sg, b.x); st[H * 2 + 1] = make_float2(a.y * sg, b.y);
          wg_wait<0>();
          reg_fence(acc);
          const bool odd = lane & 1;
          __nv_bfloat16* gp = g_ab + (size_t)((layer * 2 + m) * SEQ + r * 128 + H * 64 + frow) * DM + q * 48 + (lane & 1) * 8 + (lane & 2) * 2;
#pragma unroll
          for (int i = 0; i < 2; i++) {
#pragma unroll
            for (int b = 0; b < 6; b += 2) {
              const uint32_t va = val(acc, b, i, st[H * 2 + i]), vb = val(acc, b + 1, i, st[H * 2 + i]);
              const uint32_t o = __shfl_xor_sync(0xffffffffu, odd ? va : vb, 1);
              asm volatile("st.global.v2.u32 [%0], {%1, %2};" ::"l"(gp + i * 8 * DM + b * 8), "r"(odd ? o : va), "r"(odd ? vb : o) : "memory");
            }
          }
          __syncwarp();
          mbar_arrive_if(BAR(BAR_ABH + H), lane0);
        };
        tail(acc0, IntT<0>{});
        mbar_arrive_if(BAR(BAR_RG1 + 5), elect);
        tail(acc1, IntT<1>{});
        mbar_arrive_if(BAR(BAR_GO), elect);
#pragma unroll
        for (int i = 0; i < NB + 1; i++) mbar_arrive_cl_if(bempty + 8 * i, elect2 && i + layer < NB + 1);
        mbar_arrive_cl_if(bempty + 8 * (BAR_STG2 - BAR_BEMPTY), elect2);
#pragma unroll
        for (int i = 6; i < 9; i++) mbar_arrive_if(BAR(BAR_RG1 + i), elect);
        asm volatile("bar.sync %0, 128;" ::"r"(1 + wg) : "memory");
        const uint32_t stg = sb + OFF_A + 6 * A_SLOT + (warp * 16 + srow) * 96 + schunk * 16;
#pragma unroll
        for (int b2 = 3; b2 < 9; b2++) {
          const uint32_t ad = stg + (b2 / 3) * A_SLOT + (b2 % 3) * 32;
          stsm4(ad, val(acc0, b2 * 2, 0, st[0]), val(acc0, b2 * 2, 1, st[1]), val(acc0, b2 * 2 + 1, 0, st[0]), val(acc0, b2 * 2 + 1, 1, st[1]));
          stsm4(ad + 64 * 96, val(acc1, b2 * 2, 0, st[2]), val(acc1, b2 * 2, 1, st[3]), val(acc1, b2 * 2 + 1, 0, st[2]), val(acc1, b2 * 2 + 1, 1, st[3]));
        }
        fence_async_smem();
        __syncwarp();
        mbar_arrive_if(BAR(BAR_ABSTG), lane0);
      }
#pragma unroll 1
      for (int pi = live ? 2 - wg : 7; pi < 7; pi += 2) {
        {
          float acc0[96], acc1[96];
          int atom0;
          int seq, nt, nt2 = 0, nt3 = 0, gap = 0, gap2 = 0, fbar, rbar = BAR_RNONE, sgm = pi;
          if (pi < 4) { atom0 = (pi - 1) * 3; nt = 8; seq = pi * 16 - 16; fbar = BAR_CF; if (pi == 3) rbar = BAR_RG2; }
          else if (pi == 4) { atom0 = 0; seq = 48; nt = G3A_C1 / 2; nt2 = (G3A_C2 - G3A_C1) / 2; nt3 = 9 - G3A_C2 / 2; gap = G3B_C1; gap2 = G3B_C2 - G3B_C1; fbar = BAR_X1F; }
          else if (pi == 5) { atom0 = 3; seq = 48 + G3A_C1; nt = G3B_C1 / 2; nt2 = (G3B_C2 - G3B_C1) / 2; nt3 = 9 - G3B_C2 / 2; gap = G3A_C2 - G3A_C1; gap2 = 18 - G3A_C2; fbar = BAR_X1F; rbar = BAR_RG3B; }
          else { atom0 = 6; seq = 84; nt = 9; fbar = BAR_X1F + 3; rbar = BAR_RG3C; sgm = 10; }
          constexpr uint32_t blo0 = ((sbd + OFF_B) >> 4) | ((4096u >> 4) << 16);
          uint32_t so = (seq % (NB + 1)) * 8, ph = seq / (NB + 1) + 1 - layer;
          uint32_t alo = alo0 + ((pi == 6) ? 6 * (A_SLOT >> 4) : 0);
          uint32_t fa = BAR(fbar), ra = BAR(rbar), go = BAR(BAR_GO + sgm);
          uint32_t pso, rel, epok = 0;
          auto issue = [&](uint32_t a, auto first) {
            constexpr bool F = decltype(first)::value;
            const uint32_t blo = blo0 + so * (B_SLOT >> 7);
            wg_fence();
            wgmma_n192<1, F>(acc0, desc(a, DESC_HI_128), desc(blo, DESC_HI_128));
            wgmma_n192<1, F>(acc1, desc(a + 512, DESC_HI_128), desc(blo, DESC_HI_128));
            wgmma_n192<1, false>(acc0, desc(a + 2, DESC_HI_128), desc(blo + 128, DESC_HI_128));
            wgmma_n192<1, false>(acc1, desc(a + 514, DESC_HI_128), desc(blo + 128, DESC_HI_128));
            wg_commit();
          };
          auto advance = [&]() { so += 8; if (so == (NB + 1) * 8) { so = 0; ph++; } };
          auto enter = [&]() {
            const uint32_t t0 = mbar_test(fa, layer), t1 = mbar_test(go - 8, layer), t2 = mbar_test(bfull + so, ph);
            if (!(t0 & t1 & t2)) {
              mbar_wait(fa, layer);
              mbar_wait(go - 8, layer);
              mbar_wait(bfull + so, ph);
            }
          };
          enter();
          issue(alo, TrueT{});
          pso = so;
          advance();
          mbar_wait(bfull + so, ph);
#pragma unroll 1
          for (;;) {
            issue(alo + 4, FalseT{});
            const uint32_t cso = so;
            advance();
            alo += A_SLOT >> 4;
            if (alo == alo0 + 9 * (A_SLOT >> 4)) alo = alo0 + 3 * (A_SLOT >> 4);
            fa += 8;
            if (--nt == 0) {
              mbar_arrive_if(go, elect);
              wg_wait<1>();
              mbar_arrive_cl_if(bempty + pso, elect2);
              if (nt2 == 0 && pi >= 4) {
                const uint32_t t0 = mbar_test(BAR(BAR_STAT + 1), layer), t1 = mbar_test(BAR(BAR_CSOK), layer), t2 = mbar_test(BAR(BAR_RG3B + 2), layer);
                epok = t0 & t1 & t2;
              }
              wg_wait<0>();
              mbar_arrive_cl_if(bempty + cso, elect2);
              mbar_arrive_if(ra, elect);
              if (nt2 == 0) break;
              nt = nt2; nt2 = nt3; nt3 = 0;
              const uint32_t t = so + gap * 8;
              so = t % ((NB + 1) * 8); ph += t / ((NB + 1) * 8);
              gap = gap2;
              go += 16;
              rel = 0;
              enter();
            } else {
              const uint32_t ready = mbar_test(fa, layer) & mbar_test(bfull + so, ph);
              wg_wait<1>();
              mbar_arrive_cl_if(bempty + pso, elect2);
              rel = 1;
              if (!ready) {
                mbar_wait(fa, layer);
                mbar_wait(bfull + so, ph);
              }
            }
            issue(alo, FalseT{});
            pso = so;
            advance();
            const uint32_t ready = mbar_test(bfull + so, ph);
            wg_wait<1>();
            mbar_arrive_cl_if(bempty + cso, rel && elect2);
            mbar_arrive_if(ra, rel && elect);
            ra += 8;
            if (!ready) {
              mbar_wait(bfull + so, ph);
            }
          }
        wg_wait<0>();
        reg_fence(acc0); reg_fence(acc1);
        if (pi >= 4 && pi <= 6) {
          if (!epok) {
            mbar_wait(BAR(BAR_STAT + 1), layer);
            mbar_wait(BAR(BAR_CSOK), layer);
            mbar_wait(BAR(BAR_RG3B + 2), layer);
          }
          if (pi == 5) mbar_wait(BAR(BAR_XRD), layer);
          if (pi == 6) asm volatile("bar.sync %0, 128;" ::"r"(1 + wg) : "memory");
          float2 st[4];
          {
            const float4 b = lds128f(sb + OFF_MEAN + fpos);
            st[0].y = b.x; st[1].y = b.y; st[2].y = b.z; st[3].y = b.w;
          }
          const uint32_t cs = sb + OFF_CS1 + (lane & 3) * 592 + atom0 * 64;
          const uint32_t dst = sb + OFF_A + atom0 * A_SLOT + (warp * 16 + srow) * 128;
          float4 cn[2];
          cn[0] = lds128f(cs); cn[1] = lds128f(cs + 16);
#pragma unroll
          for (int b2 = 0; b2 < 12; b2++) {
            if ((b2 & 3) == 0 && pi == 5) mbar_wait(BAR(BAR_RG3C + 3 + (b2 >> 2)), layer);
            const float2 c0 = make_float2(cn[b2 & 1].x, cn[b2 & 1].y), c1 = make_float2(cn[b2 & 1].z, cn[b2 & 1].w);
            if (b2 + 2 < 12) cn[b2 & 1] = lds128f(cs + (b2 + 2) * 16);
            const uint32_t ad = dst + (b2 >> 2) * A_SLOT + ((((b2 & 3) * 2 + schunk) ^ (srow & 7)) << 4);
            const int o = b2 * 8;
            stsm4(ad,
                  pk_relu(fmaf(c0.x, st[0].y, acc0[o]), fmaf(c0.y, st[0].y, acc0[o + 1])),
                  pk_relu(fmaf(c0.x, st[1].y, acc0[o + 2]), fmaf(c0.y, st[1].y, acc0[o + 3])),
                  pk_relu(fmaf(c1.x, st[0].y, acc0[o + 4]), fmaf(c1.y, st[0].y, acc0[o + 5])),
                  pk_relu(fmaf(c1.x, st[1].y, acc0[o + 6]), fmaf(c1.y, st[1].y, acc0[o + 7])));
            stsm4(ad + 8192,
                  pk_relu(fmaf(c0.x, st[2].y, acc1[o]), fmaf(c0.y, st[2].y, acc1[o + 1])),
                  pk_relu(fmaf(c0.x, st[3].y, acc1[o + 2]), fmaf(c0.y, st[3].y, acc1[o + 3])),
                  pk_relu(fmaf(c1.x, st[2].y, acc1[o + 4]), fmaf(c1.y, st[2].y, acc1[o + 5])),
                  pk_relu(fmaf(c1.x, st[3].y, acc1[o + 6]), fmaf(c1.y, st[3].y, acc1[o + 7])));
            if ((b2 & 3) == 3 && (pi == 6 || b2 == 11)) {
              fence_async_smem();
              __syncwarp();
              mbar_arrive_if(BAR(BAR_HF + atom0 + (b2 >> 2)), lane0);
              if (b2 == 11 && pi != 6) { mbar_arrive_if(BAR(BAR_HF + atom0), lane0); mbar_arrive_if(BAR(BAR_HF + atom0 + 1), lane0); }
            }
          }
        } else if (pi == 3) {
          asm volatile("bar.sync %0, 128;" ::"r"(1 + wg) : "memory");
          const uint32_t dst = sb + OFF_A + 6 * A_SLOT + (warp * 16 + srow) * 128;
          float rs[4] = {0.f, 0.f, 0.f, 0.f};
#pragma unroll
          for (int b2 = 0; b2 < 12; b2++) {
            if (b2 == 8) mbar_wait(BAR(BAR_FDONE + 5), layer);
            const uint32_t ad = dst + (b2 >> 2) * A_SLOT + ((((b2 & 3) * 2 + schunk) ^ (srow & 7)) << 4);
            const int o = b2 * 8;
            stsm4(ad, pk(acc0[o], acc0[o + 1]), pk(acc0[o + 2], acc0[o + 3]), pk(acc0[o + 4], acc0[o + 5]), pk(acc0[o + 6], acc0[o + 7]));
            stsm4(ad + 8192, pk(acc1[o], acc1[o + 1]), pk(acc1[o + 2], acc1[o + 3]), pk(acc1[o + 4], acc1[o + 5]), pk(acc1[o + 6], acc1[o + 7]));
            rs[0] += (acc0[o] + acc0[o + 1]) + (acc0[o + 4] + acc0[o + 5]);
            rs[1] += (acc0[o + 2] + acc0[o + 3]) + (acc0[o + 6] + acc0[o + 7]);
            rs[2] += (acc1[o] + acc1[o + 1]) + (acc1[o + 4] + acc1[o + 5]);
            rs[3] += (acc1[o + 2] + acc1[o + 3]) + (acc1[o + 6] + acc1[o + 7]);
            if ((b2 & 3) == 3) {
              fence_async_smem();
              __syncwarp();
              if (b2 == 3) {
                if (lane0) {
                  tma_red2d(&maps.xred, sb + OFF_A + 6 * A_SLOT + warp * 2048, 384, r * 128 + warp * 16);
                  tma_red2d(&maps.xred, sb + OFF_A + 6 * A_SLOT + 8192 + warp * 2048, 384, r * 128 + 64 + warp * 16);
                  bulk_commit();
                }
              } else {
                mbar_arrive_if(BAR(BAR_FDONE + 6 + (b2 >> 2)), lane0);
              }
            }
          }
          rowsums(rs);
          bulk_wait0();
          __syncwarp();
          mbar_arrive_if(BAR(BAR_FDONE + 6), lane0);
        } else {
          flush(acc0, acc1, IntT<3>{}, pi, atom0);
        }
        }
      }
      float2 rsv[16];
      if (live) mbar_wait(BAR(BAR_RSOK), layer);
      rsf = lds128f(sb + OFF_RS + fpos);
      if (wg) {
#pragma unroll
        for (int i = 0; i < 8; i++) {
          const uint4 t = lds128(sb + OFF_RS2 + (lane & 3) * 144 + i * 16);
          rsv[i * 2] = make_float2(__uint_as_float(t.x), __uint_as_float(t.y));
          rsv[i * 2 + 1] = make_float2(__uint_as_float(t.z), __uint_as_float(t.w));
        }
      } else {
#pragma unroll
        for (int i = 0; i < 16; i++) rsv[i] = make_float2(0.f, 0.f);
      }
#pragma unroll 1
      for (int pi = live ? 8 - wg : 11; pi < 12; pi += 2) {
        {
          const int seq = (pi - 7) * 12 + 1;
          uint32_t so = (seq % NB) * 8, ph = seq / NB + layer, pso = 0, cso;
          const uint32_t go = BAR(BAR_GO + 4 + pi);
          auto enter = [&]() {
            const uint32_t t0 = mbar_test(BAR(BAR_HF), layer), t1 = mbar_test(go - 8, layer), t2 = mbar_test(bfull + so, ph);
            if (!(t0 & t1 & t2)) {
              mbar_wait(BAR(BAR_HF), layer);
              mbar_wait(go - 8, layer);
              mbar_wait(bfull + so, ph);
            }
          };
          auto advance = [&]() { cso = so; so += 8; if (so == NB * 8) { so = 0; ph++; } };
          if (pi < 11) {
            float a0[64], a1[64];
            constexpr uint32_t blo0 = ((sbd + OFF_B) >> 4) | ((6144u >> 4) << 16);
            uint32_t alo = alo0, hf = BAR(BAR_HF);
            auto issue = [&](auto jj, auto first) {
              constexpr int J = decltype(jj)::value;
              constexpr bool F = decltype(first)::value;
              const uint32_t blo = blo0 + so * (B_SLOT >> 7);
              wg_fence();
#pragma unroll
              for (int j = 0; j < 3; j++) {
                const int u = J * 3 + j;
                const uint64_t da0 = desc(alo + (u >> 2) * (A_SLOT >> 4) + (u & 3) * 2, DESC_HI_128);
                const uint64_t da1 = desc(alo + (u >> 2) * (A_SLOT >> 4) + (u & 3) * 2 + 512, DESC_HI_128);
                const uint64_t db = desc(blo + j * 128, DESC_HI_128);
                if (F && j == 0) { wgmma_n128<1, true>(a0, da0, db); wgmma_n128<1, true>(a1, da1, db); }
                else { wgmma_n128<1, false>(a0, da0, db); wgmma_n128<1, false>(a1, da1, db); }
              }
              wg_commit();
              advance();
            };
            auto next = [&](int tile, auto first) {
              uint32_t ready = mbar_test(bfull + so, ph);
              if (tile >= 0) ready &= mbar_test(hf + 8 * tile, layer);
              if (!decltype(first)::value) {
                wg_wait<1>();
                mbar_arrive_cl_if(bempty + pso, elect2);
              }
              pso = cso;
              if (!ready) {
                if (tile >= 0) mbar_wait(hf + 8 * tile, layer);
                mbar_wait(bfull + so, ph);
              }
            };
            enter();
            issue(IntT<0>{}, TrueT{});
            next(1, TrueT{});
#pragma unroll 1
            for (;;) {
              issue(IntT<1>{}, FalseT{});
              next(2, FalseT{});
              issue(IntT<2>{}, FalseT{});
              next(-1, FalseT{});
              issue(IntT<3>{}, FalseT{});
              if (alo == alo0 + 6 * (A_SLOT >> 4)) break;
              alo += 3 * (A_SLOT >> 4);
              hf += 24;
              next(0, FalseT{});
              issue(IntT<0>{}, FalseT{});
              next(1, FalseT{});
            }
            mbar_arrive_if(go, elect);
            wg_wait<1>();
            mbar_arrive_cl_if(bempty + pso, elect2);
            wg_wait<0>();
            mbar_arrive_cl_if(bempty + cso, elect2);
            reg_fence(a0); reg_fence(a1);
            flush(a0, a1, IntT<2>{}, pi, (pi - 7) * 2);
          } else {
            float a0[64];
            const uint32_t el = elect & live, el2 = elect2 & live;
            auto step = [&](int s, auto first) {
              constexpr bool F = decltype(first)::value;
              const uint32_t blo = (((sbd + OFF_B) >> 4) | (1u << 16)) + so * (B_SLOT >> 7);
              wg_fence();
#pragma unroll
              for (int j = 0; j < 6; j++) {
                const int u = s * 6 + j;
                const uint64_t dh = desc(alo0 + (u >> 2) * (A_SLOT >> 4) + (u & 3) * 2, DESC_HI_128);
                if (F && j == 0) wgmma_n128<0, true, 1>(a0, desc(blo, DESC_HI_128), dh);
                else wgmma_n128<0, false, 1>(a0, desc(blo + j * 128, DESC_HI_128), dh);
              }
              wg_commit();
              advance();
              mbar_arrive_if(go, el && s == 5);
              const uint32_t ready = mbar_test(bfull + so, ph) | (s == 5) | !live;
              if (!F) {
                wg_wait<1>();
                mbar_arrive_cl_if(bempty + pso, el2);
                mbar_arrive_if(BAR(BAR_RG4 - 1 + ((6 * s) >> 2)), el);
                mbar_arrive_if(BAR(BAR_RG4 - 2 + ((6 * s) >> 2)), el && !(s & 1));
              }
              pso = cso;
              if (!ready) mbar_wait(bfull + so, ph);
            };
            if (live) enter();
            step(0, TrueT{});
#pragma unroll 1
            for (int s = live ? 1 : 5; s < 6; s++) step(s, FalseT{});
            wg_wait<0>();
            mbar_arrive_cl_if(bempty + pso, el2);
            mbar_arrive_if(BAR(BAR_RG4 + 7), el);
            mbar_arrive_if(BAR(BAR_RG4 + 8), el);
            reg_fence(a0);
            {
              asm volatile("bar.sync %0, 128;" ::"r"(1 + wg) : "memory");
              const uint32_t tb = sb + OFF_A + 8 * A_SLOT;
              const uint32_t ad = tb + ((lane >> 4) * 8 + (lane & 7)) * 128 + (((warp * 2 + ((lane >> 3) & 1)) ^ (lane & 7)) << 4);
#pragma unroll
              for (int b2 = 0; b2 < 8; b2++) {
                const float2 f0 = rsv[b2 * 2], f1 = rsv[b2 * 2 + 1];
                const int o = b2 * 8;
                asm volatile("{\n.reg .pred p;\nsetp.ne.u32 p, %5, 0;\n@p stmatrix.sync.aligned.m8n8.x4.trans.shared.b16 [%0], {%1,%2,%3,%4};\n}" ::"r"(ad + b2 * 2048),
                             "r"(pk(a0[o] * f0.x, a0[o + 1] * f0.y)), "r"(pk(a0[o + 2] * f0.x, a0[o + 3] * f0.y)),
                             "r"(pk(a0[o + 4] * f1.x, a0[o + 5] * f1.y)), "r"(pk(a0[o + 6] * f1.x, a0[o + 7] * f1.y)), "r"(live));
              }
              fence_async_smem();
              __syncwarp();
              mbar_arrive_if(BAR(BAR_FDONE + 17), lane0 & live);
              if (it == 0) {
                const int t = tid & 127, row = t >> 1;
                const uint32_t ra = sb + OFF_A + row * 128 + ((t & 15) << 3);
                float s0 = 0.f, q0 = 0.f, s1 = 0.f, q1 = 0.f;
#pragma unroll 1
                for (int j = 0; j < 6; j++) {
                  const int k0 = (j >> 1) * 3, h = j & 1;
                  if (!h || j == 5) {
#pragma unroll 1
                    for (int i = 0; i < 3; i++) mbar_wait(BAR(h ? BAR_XFY + i : BAR_XF + k0 + i), !h);
                  }
                  const uint32_t a = ra + k0 * A_SLOT + h * 8192;
                  uint4 v[12];
#pragma unroll
                  for (int i = 0; i < 12; i++) {
                    asm volatile("ld.shared.v2.u32 {%0,%1}, [%2];" : "=r"(v[i].x), "=r"(v[i].y) : "r"((a ^ ((i & 3) << 5)) + (i >> 2) * A_SLOT) : "memory");
                    asm volatile("ld.shared.v2.u32 {%0,%1}, [%2];" : "=r"(v[i].z), "=r"(v[i].w) : "r"((a ^ (((i & 3) << 5) | 16)) + (i >> 2) * A_SLOT) : "memory");
                  }
                  float s2 = 0.f, q2 = 0.f;
#pragma unroll
                  for (int i = 0; i < 12; i += 2) { sum8(v[i], s0, q0); sum8(v[i + 1], s2, q2); }
                  s0 += s2; q0 += q2;
                  if (j >= 4) {
                    s0 += __shfl_xor_sync(0xffffffffu, s0, 1);
                    q0 += __shfl_xor_sync(0xffffffffu, q0, 1);
                    const float mean = s0 * (1.0f / DM);
                    reinterpret_cast<float*>(smem + ((t & 1) ? OFF_RS : OFF_MEAN))[frag_pos(row + h * 64)] =
                        (t & 1) ? rsqrtf(fmaxf(q0 * (1.0f / DM) - mean * mean, 0.f) + 1e-5f) : -mean;
                  }
                  { float u = s0; s0 = s1; s1 = u; u = q0; q0 = q1; q1 = u; }
                  if (h || j == 4) {
                    asm volatile("bar.sync %0, 128;" ::"r"(1 + wg) : "memory");
                    mbar_arrive_if(BAR(j == 4 ? BAR_STAT : (j == 5 ? BAR_STATY : BAR_RD + (j >> 1))), elect);
                  }
                }
              }
            }
          }
        }
      }
    }
  }
#undef BAR
}

typedef CUresult (*EncodeFn)(CUtensorMap*, CUtensorMapDataType, cuuint32_t, void*, const cuuint64_t*, const cuuint64_t*, const cuuint32_t*,
                             const cuuint32_t*, CUtensorMapInterleave, CUtensorMapSwizzle, CUtensorMapL2promotion, CUtensorMapFloatOOBfill);

void make2d(EncodeFn enc, CUtensorMap* m, const void* ptr, uint64_t inner, uint64_t outer, uint32_t bi, uint32_t bo, CUtensorMapSwizzle sw) {
  cuuint64_t d[2] = {inner, outer};
  cuuint64_t s[1] = {inner * 2};
  cuuint32_t b[2] = {bi, bo}, e[2] = {1, 1};
  enc(m, CU_TENSOR_MAP_DATA_TYPE_BFLOAT16, 2, const_cast<void*>(ptr), d, s, b, e, CU_TENSOR_MAP_INTERLEAVE_NONE, sw,
      CU_TENSOR_MAP_L2_PROMOTION_L2_128B, CU_TENSOR_MAP_FLOAT_OOB_FILL_NONE);
}
void make3d(EncodeFn enc, CUtensorMap* m, const void* ptr, uint64_t d0, uint64_t d1, uint64_t d2, uint64_t s1, uint64_t s2,
            uint32_t b0, uint32_t b1, uint32_t b2, CUtensorMapSwizzle sw) {
  cuuint64_t d[3] = {d0, d1, d2};
  cuuint64_t s[2] = {s1, s2};
  cuuint32_t b[3] = {b0, b1, b2}, e[3] = {1, 1, 1};
  enc(m, CU_TENSOR_MAP_DATA_TYPE_BFLOAT16, 3, const_cast<void*>(ptr), d, s, b, e, CU_TENSOR_MAP_INTERLEAVE_NONE, sw,
      CU_TENSOR_MAP_L2_PROMOTION_L2_128B, CU_TENSOR_MAP_FLOAT_OOB_FILL_NONE);
}

}

extern "C" void kernel_launch(void* const* d_in, const int* in_sizes, int n_in, void* d_out, int out_size) {
  (void)in_sizes; (void)n_in; (void)out_size;
  const __nv_bfloat16* x = (const __nv_bfloat16*)d_in[0];
  const __nv_bfloat16* cr = (const __nv_bfloat16*)d_in[1];
  const __nv_bfloat16* ci = (const __nv_bfloat16*)d_in[2];
  const __nv_bfloat16* dr = (const __nv_bfloat16*)d_in[3];
  const __nv_bfloat16* di = (const __nv_bfloat16*)d_in[4];
  const __nv_bfloat16* w1 = (const __nv_bfloat16*)d_in[6];
  const __nv_bfloat16* w2 = (const __nv_bfloat16*)d_in[7];
  __nv_bfloat16* out = (__nv_bfloat16*)d_out;

  void* fn = nullptr;
  cudaDriverEntryPointQueryResult qr;
  cudaGetDriverEntryPoint("cuTensorMapEncodeTiled", &fn, cudaEnableDefault, &qr);
  EncodeFn enc = (EncodeFn)fn;
  void* ab = nullptr;
  cudaGetSymbolAddress(&ab, g_ab);

  Maps maps;
  make2d(enc, &maps.xin, x, DM, SEQ, 64, 128, CU_TENSOR_MAP_SWIZZLE_128B);
  make2d(enc, &maps.xld, out, DM, SEQ, 64, 128, CU_TENSOR_MAP_SWIZZLE_128B);
  make2d(enc, &maps.xh, out, DM, SEQ, 64, 64, CU_TENSOR_MAP_SWIZZLE_128B);
  make2d(enc, &maps.xred, out, DM, SEQ, 64, 16, CU_TENSOR_MAP_SWIZZLE_128B);
  make2d(enc, &maps.cr, cr, SEQ, SEQ, 64, 128, CU_TENSOR_MAP_SWIZZLE_128B);
  make2d(enc, &maps.ci, ci, SEQ, SEQ, 64, 128, CU_TENSOR_MAP_SWIZZLE_128B);
  make3d(enc, &maps.dr, dr, DM, 192, 3, DM * 2, 192 * DM * 2, 64, 48, 3, CU_TENSOR_MAP_SWIZZLE_128B);
  make3d(enc, &maps.di, di, DM, 192, 3, DM * 2, 192 * DM * 2, 64, 48, 3, CU_TENSOR_MAP_SWIZZLE_128B);
  make3d(enc, &maps.abld, ab, 64, 4 * SEQ, DM / 64, DM * 2, 128, 64, 32, 3, CU_TENSOR_MAP_SWIZZLE_128B);
  make2d(enc, &maps.abst, ab, DM, 4 * SEQ, 48, 128, CU_TENSOR_MAP_SWIZZLE_NONE);
  make3d(enc, &maps.w1, w1, 64, DM, DFF / 64, DFF * 2, 128, 64, 32, 3, CU_TENSOR_MAP_SWIZZLE_128B);
  make3d(enc, &maps.w2, w2, 64, DFF, DM / 64, DM * 2, 128, 64, 48, 2, CU_TENSOR_MAP_SWIZZLE_128B);
  make3d(enc, &maps.w2n, w2, 64, DFF, DM / 64, DM * 2, 128, 64, 96, 1, CU_TENSOR_MAP_SWIZZLE_128B);

  cudaFuncSetAttribute(fnet_ffn_kernel, cudaFuncAttributeMaxDynamicSharedMemorySize, SMEM_BYTES);
  cudaLaunchConfig_t cfg = {};
  cfg.gridDim = dim3(NGRID);
  cfg.blockDim = dim3(384);
  cfg.dynamicSmemBytes = SMEM_BYTES;
  cfg.stream = cudaStreamPerThread;
  cudaLaunchAttribute at[1];
  at[0].id = cudaLaunchAttributeClusterDimension;
  at[0].val.clusterDim.x = 2; at[0].val.clusterDim.y = 1; at[0].val.clusterDim.z = 1;
  cfg.attrs = at;
  cfg.numAttrs = 1;
  cudaLaunchKernelEx(&cfg, fnet_ffn_kernel, maps, x, cr, ci, dr, di, out);
}
```
